```python
import torch

def _softmax(x, axis=-1):
    return torch.softmax(x, dim=axis)
def _gelu(x):
    return torch.nn.functional.gelu(x, approximate="tanh")
def _silu(x):
    return torch.nn.functional.silu(x)
def _sigmoid(x):
    return torch.sigmoid(x)
def _layernorm(x, axis=-1, eps=1e-5):
    m = x.mean(dim=axis, keepdim=True)
    v = x.var(dim=axis, keepdim=True, unbiased=False)
    return (x - m) / torch.sqrt(v + eps)
def _scatter_add(tgt, idx, src, axis=0):
    return tgt.clone().index_add_(axis, idx, src)
def _segment_sum(src, seg, n):
    out = torch.zeros((n,) + src.shape[1:], dtype=src.dtype)
    return out.index_add_(0, seg, src)
def _pad(x, pw):
    flat = tuple(v for pair in reversed(pw) for v in pair)
    return torch.nn.functional.pad(x, flat)

kernel_name = 'standalone__edge_featured_mpnn_gatedgcn__graph'

def setup_inputs():

    _w = (lambda a: (lambda t: t.to(torch.bfloat16) if t.is_floating_point() else t)(torch.as_tensor(a)))
    N, deg, D, De = 10000, 64, 64, max(16, 1)
    E = N * deg
    return {
        "x": _w((lambda *s: torch.randn(*s, dtype=torch.bfloat16) * 0.8)(N, D)),
        "e_attr": _w((lambda *s: torch.randn(*s, dtype=torch.bfloat16) * 0.8)(E, De)),
        "src": _w((lambda lo, hi, *s: torch.randint(lo, hi, s))(0, N, E).to(torch.int64)),
        "dst": _w((lambda lo, hi, *s: torch.randint(lo, hi, s))(0, N, E).to(torch.int64)),
        "w_a": _w((lambda *s: torch.randn(*s, dtype=torch.bfloat16) * 0.8)(D, D)),
        "w_b": _w((lambda *s: torch.randn(*s, dtype=torch.bfloat16) * 0.8)(D, D)),
        "w_c": _w((lambda *s: torch.randn(*s, dtype=torch.bfloat16) * 0.8)(De, D)),
        "w_u": _w((lambda *s: torch.randn(*s, dtype=torch.bfloat16) * 0.05)(D, D)),
        "w_v": _w((lambda *s: torch.randn(*s, dtype=torch.bfloat16) * 0.05)(D, D)),
    }

def reference(x, e_attr, src, dst, w_a, w_b, w_c, w_u, w_v):
    N, D = x.shape
    hv = x @ w_v
    g = x[dst] @ w_a + x[src] @ w_b + e_attr @ w_c
    eta = _sigmoid(g)
    denom = _segment_sum(eta, dst, N) + 1e-6
    eta_n = eta / denom[dst]
    agg = _segment_sum(eta_n * hv[src], dst, N)
    z = x @ w_u + agg
    relu_z = torch.where(z > 0, z, 0 * z)
    return x + relu_z
```

```cpp
#include <cuda_runtime.h>
#include <cuda_bf16.h>
#include <stdint.h>

namespace {

constexpr int N_NODES  = 10000;
constexpr int N_EDGES  = 640000;
constexpr int NB       = 132;
constexpr int NPB      = 76;
constexpr int NW       = 10;
constexpr int CHUNK    = 4864;
constexpr int CAP      = 80;
constexpr int CAPL     = 5376;
constexpr int NTHREADS = 384;
constexpr int NWARPS   = NTHREADS / 32;
constexpr int NWG      = 3;
constexpr int STAGES   = 3;
constexpr int STAGE_BYTES = 10240;
constexpr int SEG_PER_WARP = NB / NWARPS;
static_assert(NB % NWARPS == 0, "segments per warp");
static_assert(NB * NPB >= N_NODES && NB * CHUNK >= N_EDGES, "coverage");

constexpr int ACC_LD = 68;
constexpr int U_LD   = 72;
constexpr int W_LD   = 144;

constexpr int SM_STAGE = 0;
constexpr int SM_XOWN  = NWG * STAGES * STAGE_BYTES;
constexpr int SM_LIST0 = SM_XOWN + 80 * 128;
constexpr int SM_LIST1 = SM_LIST0 + CAPL * 4;
constexpr int SM_ACCD  = SM_LIST1 + CAPL * 4;
constexpr int SM_ACCN  = SM_ACCD + 80 * ACC_LD * 4;
constexpr int SM_U     = SM_ACCN + 80 * ACC_LD * 4;
constexpr int SM_AFRAG = SM_U + 80 * U_LD * 2;
constexpr int SM_ONEH  = SM_AFRAG + NW * 128 * 8;
constexpr int SM_CNT   = SM_ONEH + 160;
constexpr int SM_NCNT  = SM_CNT + 136 * 4;
constexpr int SM_NBASE = SM_NCNT + 96 * 4;
constexpr int SM_WBASE = SM_NBASE + 96 * 4;
constexpr int SM_MISC  = SM_WBASE + 16 * 4;
constexpr int SM_TOTAL = SM_MISC + 8 * 4;
static_assert(NB * CAP * 8 <= SM_XOWN, "staging fits");
static_assert(CAPL * 8 <= SM_XOWN, "extras fit");
static_assert(4 * 64 * W_LD + 16 * W_LD <= 2 * CAPL * 4, "weights fit");
static_assert(SM_TOTAL <= 227 * 1024, "smem");

constexpr int WS_A = 0, WS_B = 64 * W_LD, WS_V = 2 * 64 * W_LD, WS_U = 3 * 64 * W_LD, WS_C = 4 * 64 * W_LD;

constexpr uint32_t TAG_MASK = 0x3FFFFu;
constexpr uint32_t NULL_W1 = 127u << 25;

__device__ unsigned long long g_ticket;
__device__ __align__(128) unsigned long long g_seg[(size_t)NB * NB * CAP];

#define PROF(i) do {} while (0)

__device__ __forceinline__ void cp_async16(uint32_t dst, const void* src) {
    asm volatile("cp.async.cg.shared.global [%0], [%1], 16;" :: "r"(dst), "l"(src) : "memory");
}
__device__ __forceinline__ void cp_async16_zfill(uint32_t dst, const void* src, int sz) {
    asm volatile("cp.async.cg.shared.global [%0], [%1], 16, %2;" :: "r"(dst), "l"(src), "r"(sz) : "memory");
}
__device__ __forceinline__ void cp_commit() { asm volatile("cp.async.commit_group;" ::: "memory"); }
template <int N> __device__ __forceinline__ void cp_wait() { asm volatile("cp.async.wait_group %0;" :: "n"(N) : "memory"); }
__device__ __forceinline__ void fence_async() { asm volatile("fence.proxy.async.shared::cta;" ::: "memory"); }
__device__ __forceinline__ void wg_bar(int id) { asm volatile("bar.sync %0, 128;" :: "r"(id) : "memory"); }
__device__ __forceinline__ void wgmma_fence() { asm volatile("wgmma.fence.sync.aligned;" ::: "memory"); }
__device__ __forceinline__ void wgmma_commit() { asm volatile("wgmma.commit_group.sync.aligned;" ::: "memory"); }
template <int N> __device__ __forceinline__ void wgmma_wait() { asm volatile("wgmma.wait_group.sync.aligned %0;" :: "n"(N) : "memory"); }

__device__ __forceinline__ void ldsm_x4(uint32_t (&r)[4], uint32_t addr) {
    asm volatile("ldmatrix.sync.aligned.m8n8.x4.shared.b16 {%0,%1,%2,%3}, [%4];"
                 : "=r"(r[0]), "=r"(r[1]), "=r"(r[2]), "=r"(r[3]) : "r"(addr) : "memory");
}
__device__ __forceinline__ void ldsm_x4_t(uint32_t (&r)[4], uint32_t addr) {
    asm volatile("ldmatrix.sync.aligned.m8n8.x4.trans.shared.b16 {%0,%1,%2,%3}, [%4];"
                 : "=r"(r[0]), "=r"(r[1]), "=r"(r[2]), "=r"(r[3]) : "r"(addr) : "memory");
}
__device__ __forceinline__ uint32_t lds32(uint32_t addr) {
    uint32_t v; asm volatile("ld.shared.u32 %0, [%1];" : "=r"(v) : "r"(addr) : "memory"); return v;
}
__device__ __forceinline__ uint2 lds64(uint32_t addr) {
    uint2 v; asm volatile("ld.shared.v2.u32 {%0,%1}, [%2];" : "=r"(v.x), "=r"(v.y) : "r"(addr) : "memory"); return v;
}
__device__ __forceinline__ uint4 lds128(uint32_t addr) {
    uint4 v; asm volatile("ld.shared.v4.u32 {%0,%1,%2,%3}, [%4];" : "=r"(v.x), "=r"(v.y), "=r"(v.z), "=r"(v.w) : "r"(addr) : "memory"); return v;
}

__device__ __forceinline__ void mma_k8_zero(float* d, uint32_t a0, uint32_t a1, uint32_t b0) {
    asm volatile("mma.sync.aligned.m16n8k8.row.col.f32.bf16.bf16.f32 {%0,%1,%2,%3}, {%4,%5}, {%6}, {%7,%7,%7,%7};"
                 : "=f"(d[0]), "=f"(d[1]), "=f"(d[2]), "=f"(d[3]) : "r"(a0), "r"(a1), "r"(b0), "f"(0.f));
}
__device__ __forceinline__ void mma_k8_acc(float* d, uint32_t a0, uint32_t a1, uint32_t b0) {
    asm volatile("mma.sync.aligned.m16n8k8.row.col.f32.bf16.bf16.f32 {%0,%1,%2,%3}, {%4,%5}, {%6}, {%0,%1,%2,%3};"
                 : "+f"(d[0]), "+f"(d[1]), "+f"(d[2]), "+f"(d[3]) : "r"(a0), "r"(a1), "r"(b0));
}
__device__ __forceinline__ void mma_k16_acc(float (&d)[4], const uint32_t* a, uint32_t b0, uint32_t b1) {
    asm volatile("mma.sync.aligned.m16n8k16.row.col.f32.bf16.bf16.f32 {%0,%1,%2,%3}, {%4,%5,%6,%7}, {%8,%9}, {%0,%1,%2,%3};"
                 : "+f"(d[0]), "+f"(d[1]), "+f"(d[2]), "+f"(d[3])
                 : "r"(a[0]), "r"(a[1]), "r"(a[2]), "r"(a[3]), "r"(b0), "r"(b1));
}

__device__ __forceinline__ uint64_t desc_sw128(uint32_t saddr) {
    return (uint64_t)((saddr & 0x3FFFF) >> 4) | (1ull << 16) | (64ull << 32) | (1ull << 62);
}
__device__ __forceinline__ uint64_t desc_sw32(uint32_t saddr) {
    return (uint64_t)((saddr & 0x3FFFF) >> 4) | (1ull << 16) | (16ull << 32) | (3ull << 62);
}

template <int SCALE_D>
__device__ __forceinline__ void wgmma_n64(float (&d)[32], const uint32_t (&a)[4], uint64_t desc) {
    asm volatile(
        "wgmma.mma_async.sync.aligned.m64n64k16.f32.bf16.bf16 "
        "{%0,%1,%2,%3,%4,%5,%6,%7,%8,%9,%10,%11,%12,%13,%14,%15,"
        "%16,%17,%18,%19,%20,%21,%22,%23,%24,%25,%26,%27,%28,%29,%30,%31}, "
        "{%32,%33,%34,%35}, %36, %37, 1, 1, 0;"
        : "+f"(d[0]), "+f"(d[1]), "+f"(d[2]), "+f"(d[3]), "+f"(d[4]), "+f"(d[5]), "+f"(d[6]), "+f"(d[7]),
          "+f"(d[8]), "+f"(d[9]), "+f"(d[10]), "+f"(d[11]), "+f"(d[12]), "+f"(d[13]), "+f"(d[14]), "+f"(d[15]),
          "+f"(d[16]), "+f"(d[17]), "+f"(d[18]), "+f"(d[19]), "+f"(d[20]), "+f"(d[21]), "+f"(d[22]), "+f"(d[23]),
          "+f"(d[24]), "+f"(d[25]), "+f"(d[26]), "+f"(d[27]), "+f"(d[28]), "+f"(d[29]), "+f"(d[30]), "+f"(d[31])
        : "r"(a[0]), "r"(a[1]), "r"(a[2]), "r"(a[3]), "l"(desc), "n"(SCALE_D));
}
template <int SCALE_D>
__device__ __forceinline__ void wgmma_n80(float (&d)[40], const uint32_t (&a)[4], uint64_t desc) {
    asm volatile(
        "wgmma.mma_async.sync.aligned.m64n80k16.f32.bf16.bf16 "
        "{%0,%1,%2,%3,%4,%5,%6,%7,%8,%9,%10,%11,%12,%13,%14,%15,"
        "%16,%17,%18,%19,%20,%21,%22,%23,%24,%25,%26,%27,%28,%29,%30,%31,"
        "%32,%33,%34,%35,%36,%37,%38,%39}, "
        "{%40,%41,%42,%43}, %44, %45, 1, 1, 0;"
        : "+f"(d[0]), "+f"(d[1]), "+f"(d[2]), "+f"(d[3]), "+f"(d[4]), "+f"(d[5]), "+f"(d[6]), "+f"(d[7]),
          "+f"(d[8]), "+f"(d[9]), "+f"(d[10]), "+f"(d[11]), "+f"(d[12]), "+f"(d[13]), "+f"(d[14]), "+f"(d[15]),
          "+f"(d[16]), "+f"(d[17]), "+f"(d[18]), "+f"(d[19]), "+f"(d[20]), "+f"(d[21]), "+f"(d[22]), "+f"(d[23]),
          "+f"(d[24]), "+f"(d[25]), "+f"(d[26]), "+f"(d[27]), "+f"(d[28]), "+f"(d[29]), "+f"(d[30]), "+f"(d[31]),
          "+f"(d[32]), "+f"(d[33]), "+f"(d[34]), "+f"(d[35]), "+f"(d[36]), "+f"(d[37]), "+f"(d[38]), "+f"(d[39])
        : "r"(a[0]), "r"(a[1]), "r"(a[2]), "r"(a[3]), "l"(desc), "n"(SCALE_D));
}
template <int NREG>
__device__ __forceinline__ void reg_fence(float (&d)[NREG]) {
    #pragma unroll
    for (int i = 0; i < NREG; i++) asm volatile("" : "+f"(d[i]) :: "memory");
}

__device__ __forceinline__ uint32_t pack_bf16(float lo, float hi) {
    uint32_t d; asm("cvt.rn.bf16x2.f32 %0, %1, %2;" : "=r"(d) : "f"(hi), "f"(lo)); return d;
}
__device__ __forceinline__ uint32_t pack_bf16_sat(float lo, float hi) {
    uint32_t d; asm("cvt.rn.satfinite.bf16x2.f32 %0, %1, %2;" : "=r"(d) : "f"(hi), "f"(lo)); return d;
}
__device__ __forceinline__ uint32_t fma_bf2(uint32_t a, uint32_t b, uint32_t c) {
    uint32_t d; asm("fma.rn.bf16x2 %0, %1, %2, %3;" : "=r"(d) : "r"(a), "r"(b), "r"(c)); return d;
}
__device__ __forceinline__ uint32_t mul_bf2(uint32_t a, uint32_t b) {
    uint32_t d; asm("mul.rn.bf16x2 %0, %1, %2;" : "=r"(d) : "r"(a), "r"(b)); return d;
}
__device__ __forceinline__ float ex2f(float x) {
    float y; asm("ex2.approx.ftz.f32 %0, %1;" : "=f"(y) : "f"(x)); return y;
}
__device__ __forceinline__ uint32_t sigmoid4_pair(float g0, float g1) {
    const float NL2E = -1.4426950408889634f;
    float u0 = ex2f(g0 * NL2E), u1 = ex2f(g1 * NL2E);
    uint32_t u  = pack_bf16_sat(u0, u1);
    uint32_t na = fma_bf2(u, 0xBE80BE80u, 0xBE80BE80u);
    uint32_t r0 = 0xFEF3FEF3u - na;
    uint32_t e  = fma_bf2(na, r0, 0x3F803F80u);
    uint32_t t  = fma_bf2(e, e, e);
    return fma_bf2(r0, t, r0);
}

__device__ __forceinline__ void ld_relaxed_v2(unsigned long long& a, unsigned long long& b, const unsigned long long* p) {
    asm volatile("ld.relaxed.gpu.global.v2.b64 {%0,%1}, [%2];" : "=l"(a), "=l"(b) : "l"(p) : "memory");
}
__device__ __forceinline__ void st_relaxed_v2(unsigned long long* p, unsigned long long a, unsigned long long b) {
    asm volatile("st.relaxed.gpu.global.v2.b64 [%0], {%1,%2};" :: "l"(p), "l"(a), "l"(b) : "memory");
}

__global__ void __launch_bounds__(NTHREADS, 1)
gatedgcn_kernel(const __nv_bfloat16* __restrict__ x, const __nv_bfloat16* __restrict__ e_attr,
                const int* __restrict__ src, const int* __restrict__ dst,
                const __nv_bfloat16* __restrict__ w_a, const __nv_bfloat16* __restrict__ w_b,
                const __nv_bfloat16* __restrict__ w_c, const __nv_bfloat16* __restrict__ w_u,
                const __nv_bfloat16* __restrict__ w_v, __nv_bfloat16* __restrict__ out) {
    extern __shared__ __align__(1024) unsigned char smem[];
    const uint32_t sb = (uint32_t)__cvta_generic_to_shared(smem);
    const int tid = threadIdx.x, lane = tid & 31, warp = tid >> 5;
    const int wg = tid >> 7, wtid = tid & 127, wwarp = warp & 3;
    const int cta = blockIdx.x;
    const int node0 = cta * NPB;

    int* s_cnt   = (int*)(smem + SM_CNT);
    int* s_ncnt  = (int*)(smem + SM_NCNT);
    int* s_nbase = (int*)(smem + SM_NBASE);
    int* s_wbase = (int*)(smem + SM_WBASE);
    volatile int* s_misc = (volatile int*)(smem + SM_MISC);
    unsigned long long* s_stage = (unsigned long long*)(smem + SM_STAGE);
    uint32_t* s_list0 = (uint32_t*)(smem + SM_LIST0);
    uint32_t* s_list1 = (uint32_t*)(smem + SM_LIST1);
    float* s_accd = (float*)(smem + SM_ACCD);
    float* s_accn = (float*)(smem + SM_ACCN);

    PROF(0);
    unsigned long long ticket = 0;
    if (tid == 0) ticket = atomicAdd(&g_ticket, 1ull);

    const int ebase = cta * CHUNK;
    const int nvec = (min(CHUNK, N_EDGES - ebase)) >> 2;
    int4 dv[4], sv[4];
    #pragma unroll
    for (int k = 0; k < 4; k++) {
        int v = tid + k * NTHREADS;
        if (v < nvec) {
            dv[k] = __ldg((const int4*)(dst + ebase) + v);
            sv[k] = __ldg((const int4*)(src + ebase) + v);
        }
    }
    {
        const uint32_t wsb = sb + SM_LIST0;
        for (int i = tid; i < 4 * 512 + 128; i += NTHREADS) {
            int m = i >> 9, r = (i >> 3) & 63, c = i & 7;
            const __nv_bfloat16* wsrc = m == 0 ? w_a : m == 1 ? w_b : m == 2 ? w_v : m == 3 ? w_u : w_c;
            cp_async16(wsb + m * 64 * W_LD + r * W_LD + c * 16, wsrc + r * 64 + c * 8);
        }
        for (int i = tid; i < 80 * 8; i += NTHREADS) {
            int r = i >> 3, c = i & 7;
            int node = node0 + r;
            bool ok = r < NPB && node < N_NODES;
            cp_async16_zfill(sb + SM_XOWN + r * 128 + ((c ^ (r & 7)) << 4), x + (size_t)(ok ? node : 0) * 64 + c * 8, ok ? 16 : 0);
        }
        cp_commit();
    }
    if (warp == NWARPS - 1) {
        const int nbytes = nvec * 4 * 32;
        const int piece = 4864;
        int off = lane * piece;
        if (off < nbytes) {
            int sz = min(piece, nbytes - off);
            asm volatile("cp.async.bulk.prefetch.L2.global [%0], %1;"
                         :: "l"((const char*)e_attr + (size_t)ebase * 32 + off), "r"(sz) : "memory");
        }
    }
    if (tid < 136) s_cnt[tid] = 0;
    if (tid < 96) s_ncnt[tid] = 0;
    if (tid < 36) {
        int r = tid >> 2, wd = tid & 3;
        uint32_t v = 0;
        if (r < 8 && (r >> 1) == wd) v = (r & 1) ? 0x3F800000u : 0x00003F80u;
        ((uint32_t*)(smem + SM_ONEH))[tid] = v;
    }
    for (int i = tid; i < 2 * 80 * ACC_LD / 4; i += NTHREADS) ((float4*)s_accd)[i] = make_float4(0.f, 0.f, 0.f, 0.f);
    if (tid == 0) {
        s_misc[0] = (int)(((uint32_t)(ticket / NB) + 1u) & TAG_MASK);
        s_misc[1] = 0;
        s_misc[2] = 0;
    }
    __syncthreads();
    const uint32_t tag = (uint32_t)s_misc[0];
    PROF(1);

    #pragma unroll
    for (int k = 0; k < 4; k++) {
        int v = tid + k * NTHREADS;
        if (v < nvec) {
            const int dd[4] = {dv[k].x, dv[k].y, dv[k].z, dv[k].w};
            const int ss[4] = {sv[k].x, sv[k].y, sv[k].z, sv[k].w};
            #pragma unroll
            for (int j = 0; j < 4; j++) {
                uint32_t d = (uint32_t)dd[j];
                uint32_t b = d / NPB, dl = d - b * NPB;
                int rank = atomicAdd(&s_cnt[b], 1);
                uint32_t lo = (uint32_t)(ebase + v * 4 + j) * 32u | (dl << 25);
                uint32_t hi = (uint32_t)ss[j] | (tag << 14);
                if (rank < CAP - 1) s_stage[b * CAP + 1 + rank] = ((unsigned long long)hi << 32) | lo;
            }
        }
    }
    __syncthreads();
    PROF(2);
    {
        const unsigned long long filler = (unsigned long long)(tag << 14) << 32;
        #pragma unroll
        for (int k = 0; k < SEG_PER_WARP; k++) {
            const int b = warp + k * NWARPS;
            const int cnt = s_cnt[b];
            unsigned long long* gp = g_seg + ((size_t)b * NB + cta) * CAP;
            if (cnt > 63) {
                if (lane < (CAP - 64) / 2) {
                    ulonglong2 v = *(const ulonglong2*)(s_stage + b * CAP + 64 + 2 * lane);
                    st_relaxed_v2(gp + 64 + 2 * lane, v.x, v.y);
                }
                __threadfence();
                __syncwarp();
            }
            ulonglong2 v = *(const ulonglong2*)(s_stage + b * CAP + 2 * lane);
            if (2 * lane > cnt) v.x = filler;
            if (2 * lane + 1 > cnt) v.y = filler;
            if (lane == 0) v.x = filler | (unsigned long long)(uint32_t)cnt;
            st_relaxed_v2(gp + 2 * lane, v.x, v.y);
        }
    }
    PROF(3);

    cp_wait<0>();
    fence_async();
    __syncthreads();
    uint32_t wb[4][4], wv[4][4], wc[4];
    {
        const uint32_t wl = sb + SM_LIST0 + ((lane & 7) + ((lane >> 4) << 3)) * W_LD + (wwarp * 16 + ((lane >> 3) & 1) * 8) * 2;
        #pragma unroll
        for (int k = 0; k < 4; k++) {
            ldsm_x4_t(wb[k], wl + WS_B + k * 16 * W_LD);
            ldsm_x4_t(wv[k], wl + WS_V + k * 16 * W_LD);
        }
        ldsm_x4_t(wc, wl + WS_C);
        if (wg < 2) {
            uint32_t wn[4][4];
            #pragma unroll
            for (int k = 0; k < 4; k++) ldsm_x4_t(wn[k], wl + (wg == 0 ? WS_A : WS_U) + k * 16 * W_LD);
            float d[40];
            const uint64_t dx = desc_sw128(sb + SM_XOWN);
            wgmma_fence();
            wgmma_n80<0>(d, wn[0], dx);
            wgmma_n80<1>(d, wn[1], dx + 2);
            wgmma_n80<1>(d, wn[2], dx + 4);
            wgmma_n80<1>(d, wn[3], dx + 6);
            wgmma_commit();
            wgmma_wait<0>();
            reg_fence(d);
            if (wg == 0) {
                #pragma unroll
                for (int w = 0; w < NW; w++) {
                    uint2 v;
                    v.x = pack_bf16(d[4 * w + 0], d[4 * w + 1]);
                    v.y = pack_bf16(d[4 * w + 2], d[4 * w + 3]);
                    *(uint2*)(smem + SM_AFRAG + (w * 128 + wtid) * 8) = v;
                }
            } else {
                __nv_bfloat16* su = (__nv_bfloat16*)(smem + SM_U);
                const int f = wwarp * 16 + (lane >> 2);
                #pragma unroll
                for (int w = 0; w < NW; w++) {
                    const int n = w * 8 + (lane & 3) * 2;
                    su[n * U_LD + f]           = __float2bfloat16(d[4 * w + 0]);
                    su[(n + 1) * U_LD + f]     = __float2bfloat16(d[4 * w + 1]);
                    su[n * U_LD + f + 8]       = __float2bfloat16(d[4 * w + 2]);
                    su[(n + 1) * U_LD + f + 8] = __float2bfloat16(d[4 * w + 3]);
                }
            }
        }
    }
    PROF(4);

    bool slow = false;
    int scan_pos = 0;
    while (true) {
        unsigned long long rec[SEG_PER_WARP][2];
        if (!slow) {
            const unsigned long long* gp = g_seg + ((size_t)cta * NB + warp) * CAP + 2 * lane;
            #pragma unroll
            for (int k = 0; k < SEG_PER_WARP; k++) ld_relaxed_v2(rec[k][0], rec[k][1], gp + (size_t)k * NWARPS * CAP);
            #pragma unroll
            for (int k = 0; k < SEG_PER_WARP; k++) {
                int cnt;
                int tries = 0;
                while (true) {
                    const uint32_t t0 = (uint32_t)(rec[k][0] >> 46), t1 = (uint32_t)(rec[k][1] >> 46);
                    if (__all_sync(0xffffffffu, t0 == tag && t1 == tag)) { cnt = __shfl_sync(0xffffffffu, (int)(uint32_t)rec[k][0], 0); break; }
                    if (++tries > 20000) { cnt = 1 << 20; break; }
                    ld_relaxed_v2(rec[k][0], rec[k][1], gp + (size_t)k * NWARPS * CAP);
                }
                if (cnt > CAP - 1) {
                    s_misc[1] = 1;
                    cnt = 0;
                } else if (cnt > 63) {
                    __threadfence();
                    if (lane < (CAP - 64) / 2) {
                        unsigned long long a, b;
                        ld_relaxed_v2(a, b, gp + (size_t)k * NWARPS * CAP + 64);
                        const int s0 = 64 + 2 * lane;
                        if (s0 <= cnt) {
                            int r = atomicAdd(&s_ncnt[(uint32_t)a >> 25], 1);
                            int p = atomicAdd((int*)&s_misc[2], 1);
                            s_stage[p] = (a & 0x00003FFFFFFFFFFFull) | ((unsigned long long)r << 46);
                        }
                        if (s0 + 1 <= cnt) {
                            int r = atomicAdd(&s_ncnt[(uint32_t)b >> 25], 1);
                            int p = atomicAdd((int*)&s_misc[2], 1);
                            s_stage[p] = (b & 0x00003FFFFFFFFFFFull) | ((unsigned long long)r << 46);
                        }
                    }
                }
                #pragma unroll
                for (int j = 0; j < 2; j++) {
                    const int s = 2 * lane + j;
                    uint32_t r = TAG_MASK;
                    if (s >= 1 && s <= cnt) r = (uint32_t)atomicAdd(&s_ncnt[(uint32_t)rec[k][j] >> 25], 1);
                    rec[k][j] = (rec[k][j] & 0x00003FFFFFFFFFFFull) | ((unsigned long long)r << 46);
                }
            }
        } else {
            while (scan_pos < N_EDGES) {
                if (s_misc[2] + NTHREADS * 4 > CAPL) break;
                __syncthreads();
                const int v = (scan_pos >> 2) + tid;
                if (v < N_EDGES / 4) {
                    const int4 d4 = __ldg((const int4*)dst + v);
                    const int dd[4] = {d4.x, d4.y, d4.z, d4.w};
                    #pragma unroll
                    for (int j = 0; j < 4; j++) {
                        const uint32_t dl = (uint32_t)(dd[j] - node0);
                        if (dl < (uint32_t)NPB) {
                            const int e = v * 4 + j;
                            const uint32_t s = (uint32_t)__ldg(src + e);
                            int r = atomicAdd(&s_ncnt[dl], 1);
                            int p = atomicAdd((int*)&s_misc[2], 1);
                            s_stage[p] = ((unsigned long long)(s | ((uint32_t)r << 14)) << 32) | ((uint32_t)e * 32u | (dl << 25));
                        }
                    }
                }
                scan_pos += NTHREADS * 4;
                __syncthreads();
            }
        }
        __syncthreads();
        PROF(5);
        if (warp == 0) {
            int c0 = s_ncnt[3 * lane], c1 = s_ncnt[3 * lane + 1], c2 = s_ncnt[3 * lane + 2];
            int s = c0 + c1 + c2, incl = s;
            #pragma unroll
            for (int o = 1; o < 32; o <<= 1) { int t = __shfl_up_sync(0xffffffffu, incl, o); if (lane >= o) incl += t; }
            int ex = incl - s;
            s_nbase[3 * lane] = ex; s_nbase[3 * lane + 1] = ex + c0; s_nbase[3 * lane + 2] = ex + c0 + c1;
            __syncwarp();
            if (lane <= NW) s_wbase[lane] = s_nbase[lane * 8];
        }
        __syncthreads();
        const int total = s_wbase[NW];
        if (!slow && (s_misc[1] != 0 || total > CAPL)) {
            slow = true;
            __syncthreads();
            if (tid < 96) s_ncnt[tid] = 0;
            if (tid == 0) s_misc[2] = 0;
            __syncthreads();
            continue;
        }
        if (!slow) {
            #pragma unroll
            for (int k = 0; k < SEG_PER_WARP; k++) {
                #pragma unroll
                for (int j = 0; j < 2; j++) {
                    const uint32_t lo = (uint32_t)rec[k][j], hi = (uint32_t)(rec[k][j] >> 32);
                    const uint32_t r = hi >> 14;
                    if (r != TAG_MASK) {
                        const int p = s_nbase[lo >> 25] + (int)r;
                        s_list0[p] = (hi & 0x3FFFu) << 7;
                        s_list1[p] = lo;
                    }
                }
            }
        }
        {
            const int nex = s_misc[2];
            for (int i = tid; i < nex; i += NTHREADS) {
                const unsigned long long rr = s_stage[i];
                const uint32_t lo = (uint32_t)rr, hi = (uint32_t)(rr >> 32);
                const int p = s_nbase[lo >> 25] + (int)(hi >> 14);
                s_list0[p] = (hi & 0x3FFFu) << 7;
                s_list1[p] = lo;
            }
            const int ntile_ = (total + 63) >> 6;
            if (tid < 64 && total + tid < ntile_ * 64) { s_list0[total + tid] = 0; s_list1[total + tid] = NULL_W1; }
        }
        __syncthreads();
        PROF(6);

        {
            const int ntile = (total + 63) >> 6;
            const int t0 = (ntile * wg) / NWG, t1 = (ntile * (wg + 1)) / NWG;
            const uint32_t stage0 = sb + SM_STAGE + wg * STAGES * STAGE_BYTES;
            const int gc = wtid & 7, gg = wtid >> 3;
            const char* xg = (const char*)x + gc * 16;
            const char* eg = (const char*)e_attr + (wtid & 1) * 16;
            const uint32_t xdst = gg * 512 + ((gc ^ ((gg & 1) << 2)) << 4);
            const uint32_t edst = 8192 + (wtid >> 1) * 32 + (((wtid & 1) ^ ((wtid >> 3) & 1)) << 4);
            const uint32_t l0a = sb + SM_LIST0 + gg * 16;
            const uint32_t l1a = sb + SM_LIST1 + (wtid >> 1) * 4;
            const uint32_t l1b = sb + SM_LIST1 + lane * 4;

            auto issue = [&](int t, uint32_t st) {
                if (t < t1) {
                    const uint4 o = lds128(l0a + t * 256);
                    const uint32_t eo = lds32(l1a + t * 256) & 0x01FFFFFFu;
                    cp_async16(st + xdst, xg + o.x);
                    cp_async16(st + 128 + (xdst ^ 16), xg + o.y);
                    cp_async16(st + 256 + (xdst ^ 32), xg + o.z);
                    cp_async16(st + 384 + (xdst ^ 48), xg + o.w);
                    cp_async16(st + edst, eg + eo);
                }
                cp_commit();
            };
            #pragma unroll
            for (int s = 0; s < STAGES - 1; s++) issue(t0 + s, stage0 + s * STAGE_BYTES);

            int wcur = 0;
            float sd[4] = {0.f, 0.f, 0.f, 0.f}, sn[4] = {0.f, 0.f, 0.f, 0.f};
            const int frow = wwarp * 16 + (lane >> 2);
            auto flush = [&](int w) {
                const int n = w * 8 + (lane & 3) * 2;
                atomicAdd(&s_accd[n * ACC_LD + frow], sd[0]);
                atomicAdd(&s_accd[(n + 1) * ACC_LD + frow], sd[1]);
                atomicAdd(&s_accd[n * ACC_LD + frow + 8], sd[2]);
                atomicAdd(&s_accd[(n + 1) * ACC_LD + frow + 8], sd[3]);
                atomicAdd(&s_accn[n * ACC_LD + frow], sn[0]);
                atomicAdd(&s_accn[(n + 1) * ACC_LD + frow], sn[1]);
                atomicAdd(&s_accn[n * ACC_LD + frow + 8], sn[2]);
                atomicAdd(&s_accn[(n + 1) * ACC_LD + frow + 8], sn[3]);
                #pragma unroll
                for (int i = 0; i < 4; i++) { sd[i] = 0.f; sn[i] = 0.f; }
            };
            if (t0 < t1) { while (s_wbase[wcur + 1] <= t0 * 64) wcur++; }
            int wnext_pos = s_wbase[wcur + 1];
            int cs = 0;
            const uint32_t oneh = sb + SM_ONEH;
            for (int t = t0; t < t1; t++) {
                const int tstart = t * 64;
                const int tend = min(tstart + 64, total);
                while (wnext_pos <= tstart) { flush(wcur); wcur++; wnext_pos = s_wbase[wcur + 1]; }
                const uint32_t dA = (lds32(l1b + t * 256) >> 21) & 0x7F0u;
                const uint32_t dB = (lds32(l1b + t * 256 + 128) >> 21) & 0x7F0u;
                float ag[32], ah[32];
                uint32_t aA = oneh + min(dA - wcur * 128u, 128u), aB = oneh + min(dB - wcur * 128u, 128u);
                {
                    uint32_t oh[4];
                    const uint2 af = lds64(sb + SM_AFRAG + (wcur * 128 + wtid) * 8);
                    ldsm_x4(oh, aA);
                    #pragma unroll
                    for (int j = 0; j < 4; j++) mma_k8_zero(&ag[4 * j], af.x, af.y, oh[j]);
                    ldsm_x4(oh, aB);
                    #pragma unroll
                    for (int j = 0; j < 4; j++) mma_k8_zero(&ag[16 + 4 * j], af.x, af.y, oh[j]);
                }
                if (wnext_pos < tend) {
                    int w = wcur, np = wnext_pos;
                    while (np < tend) {
                        w++;
                        np = s_wbase[w + 1];
                        uint32_t oh[4];
                        const uint2 af = lds64(sb + SM_AFRAG + (w * 128 + wtid) * 8);
                        ldsm_x4(oh, oneh + min(dA - w * 128u, 128u));
                        #pragma unroll
                        for (int j = 0; j < 4; j++) mma_k8_acc(&ag[4 * j], af.x, af.y, oh[j]);
                        ldsm_x4(oh, oneh + min(dB - w * 128u, 128u));
                        #pragma unroll
                        for (int j = 0; j < 4; j++) mma_k8_acc(&ag[16 + 4 * j], af.x, af.y, oh[j]);
                    }
                }
                cp_wait<STAGES - 2>();
                fence_async();
                wg_bar(1 + wg);
                const uint32_t st = stage0 + cs * STAGE_BYTES;
                const uint64_t dx = desc_sw128(st), de = desc_sw32(st + 8192);
                wgmma_fence();
                wgmma_n64<1>(ag, wb[0], dx);
                wgmma_n64<1>(ag, wb[1], dx + 2);
                wgmma_n64<1>(ag, wb[2], dx + 4);
                wgmma_n64<1>(ag, wb[3], dx + 6);
                wgmma_n64<1>(ag, wc, de);
                wgmma_commit();
                wgmma_n64<0>(ah, wv[0], dx);
                wgmma_n64<1>(ah, wv[1], dx + 2);
                wgmma_n64<1>(ah, wv[2], dx + 4);
                wgmma_n64<1>(ah, wv[3], dx + 6);
                wgmma_commit();
                {
                    const int ps = cs == 0 ? STAGES - 1 : cs - 1;
                    issue(t + STAGES - 1, stage0 + ps * STAGE_BYTES);
                }
                uint32_t pe[16], pp[16];
                wgmma_wait<1>();
                reg_fence(ag);
                #pragma unroll
                for (int i = 0; i < 16; i++) pe[i] = sigmoid4_pair(ag[2 * i], ag[2 * i + 1]);
                wgmma_wait<0>();
                reg_fence(ah);
                #pragma unroll
                for (int i = 0; i < 16; i++) pp[i] = mul_bf2(pe[i], pack_bf16(ah[2 * i], ah[2 * i + 1]));
                while (true) {
                    uint32_t ot[4];
                    ldsm_x4_t(ot, aA);
                    mma_k16_acc(sd, &pe[0], ot[0], ot[1]);
                    mma_k16_acc(sn, &pp[0], ot[0], ot[1]);
                    mma_k16_acc(sd, &pe[4], ot[2], ot[3]);
                    mma_k16_acc(sn, &pp[4], ot[2], ot[3]);
                    ldsm_x4_t(ot, aB);
                    mma_k16_acc(sd, &pe[8], ot[0], ot[1]);
                    mma_k16_acc(sn, &pp[8], ot[0], ot[1]);
                    mma_k16_acc(sd, &pe[12], ot[2], ot[3]);
                    mma_k16_acc(sn, &pp[12], ot[2], ot[3]);
                    if (wnext_pos >= tend) break;
                    flush(wcur);
                    wcur++;
                    wnext_pos = s_wbase[wcur + 1];
                    aA = oneh + min(dA - wcur * 128u, 128u);
                    aB = oneh + min(dB - wcur * 128u, 128u);
                }
                cs = cs == STAGES - 1 ? 0 : cs + 1;
            }
            if (t0 < t1) flush(wcur);
            cp_wait<0>();
        }
        __syncthreads();
        PROF(7);
        if (!slow || scan_pos >= N_EDGES) break;
        if (tid < 96) s_ncnt[tid] = 0;
        if (tid == 0) s_misc[2] = 0;
        __syncthreads();
    }

    for (int i = tid; i < NPB * 8; i += NTHREADS) {
        const int n = i >> 3, c = i & 7;
        const int node = node0 + n;
        if (node < N_NODES) {
            const float4 d0 = *(const float4*)(s_accd + n * ACC_LD + c * 8), d1 = *(const float4*)(s_accd + n * ACC_LD + c * 8 + 4);
            const float4 n0 = *(const float4*)(s_accn + n * ACC_LD + c * 8), n1 = *(const float4*)(s_accn + n * ACC_LD + c * 8 + 4);
            const uint4 uu = *(const uint4*)(smem + SM_U + (n * U_LD + c * 8) * 2);
            const uint4 xx = *(const uint4*)(smem + SM_XOWN + n * 128 + ((c ^ (n & 7)) << 4));
            const float den[8] = {d0.x, d0.y, d0.z, d0.w, d1.x, d1.y, d1.z, d1.w};
            const float num[8] = {n0.x, n0.y, n0.z, n0.w, n1.x, n1.y, n1.z, n1.w};
            const uint32_t uw[4] = {uu.x, uu.y, uu.z, uu.w}, xw[4] = {xx.x, xx.y, xx.z, xx.w};
            uint32_t ow[4];
            #pragma unroll
            for (int j = 0; j < 4; j++) {
                const float z0 = __uint_as_float(uw[j] << 16) + num[2 * j] / (den[2 * j] + 4e-6f);
                const float z1 = __uint_as_float(uw[j] & 0xFFFF0000u) + num[2 * j + 1] / (den[2 * j + 1] + 4e-6f);
                const float o0 = __uint_as_float(xw[j] << 16) + fmaxf(z0, 0.f);
                const float o1 = __uint_as_float(xw[j] & 0xFFFF0000u) + fmaxf(z1, 0.f);
                ow[j] = pack_bf16(o0, o1);
            }
            *(uint4*)(out + (size_t)node * 64 + c * 8) = make_uint4(ow[0], ow[1], ow[2], ow[3]);
        }
    }
    PROF(8);
}

}

extern "C" void kernel_launch(void* const* d_in, const int* in_sizes, int n_in, void* d_out, int out_size) {
    (void)in_sizes; (void)n_in; (void)out_size;
    cudaFuncSetAttribute(gatedgcn_kernel, cudaFuncAttributeMaxDynamicSharedMemorySize, SM_TOTAL);
    gatedgcn_kernel<<<NB, NTHREADS, SM_TOTAL>>>(
        (const __nv_bfloat16*)d_in[0], (const __nv_bfloat16*)d_in[1], (const int*)d_in[2], (const int*)d_in[3],
        (const __nv_bfloat16*)d_in[4], (const __nv_bfloat16*)d_in[5], (const __nv_bfloat16*)d_in[6],
        (const __nv_bfloat16*)d_in[7], (const __nv_bfloat16*)d_in[8], (__nv_bfloat16*)d_out);
}
```

```cpp
#include <cuda_runtime.h>
#include <cuda_bf16.h>
#include <stdint.h>

namespace {

constexpr int N_NODES  = 10000;
constexpr int N_EDGES  = 640000;
constexpr int NB       = 132;
constexpr int NPB      = 76;
constexpr int CHUNK    = 4864;
constexpr int UMAIN    = 20;
constexpr int UTAIL    = 8;
constexpr int SEGCAP   = 3 * (UMAIN + UTAIL);
constexpr int SEG_LD   = SEGCAP + 1;
constexpr int CAPN     = 112;
constexpr int LIST_LD  = (CAPN + 1) * 8;
constexpr int NTHREADS = 512;
constexpr int NWARPS   = NTHREADS / 32;
constexpr int NET      = 384;
constexpr int SPP      = NET / UMAIN;
constexpr int UPT      = (NB + SPP - 1) / SPP;
static_assert(NB * NPB > N_NODES && NB * CHUNK >= N_EDGES, "coverage");

constexpr int U_LD = 144;
constexpr int T_LD = 272;

constexpr int SM_XOWN  = 0;
constexpr int SM_LIST  = SM_XOWN + 80 * 128;
constexpr int SM_STAGE = SM_LIST;
constexpr int NULLT    = NPB * LIST_LD;
constexpr int SM_T     = SM_LIST + NULLT - 80 * T_LD;
constexpr int SM_W     = (SM_LIST + NULLT + 128 + 1023) / 1024 * 1024;
constexpr int W_BYTES  = (4 * 64 + 16) * 128;
constexpr int SM_IEA   = SM_W;
constexpr int SM_U     = SM_W + W_BYTES;
constexpr int SM_WCF   = SM_U + 80 * U_LD;
constexpr int SM_CNT   = SM_WCF + 2048;
constexpr int SM_NCNT  = SM_CNT + 136 * 4;
constexpr int SM_MISC  = SM_NCNT + 80 * 4;
constexpr int SM_TOTAL = SM_MISC + 8 * 4;
static_assert(SM_STAGE + NB * SEG_LD * 4 <= SM_T && SM_T % 16 == 0, "staging fits");
static_assert(SM_W % 16 == 0 && NULLT % 16 == 0, "alignment");
static_assert((unsigned long long)CHUNK * NPB * N_NODES <= 0xFFFFFFFFull, "record fits 32 bits");
static_assert(80 * U_LD <= 16384, "IEA fits");
static_assert(SM_TOTAL <= 134144 - 256, "fits the 132 KB carve-out");

constexpr int WS_B = 0, WS_V = 8192, WS_A = 16384, WS_U = 24576, WS_C = 32768;

constexpr uint32_t NULL_W0 = (uint32_t)N_NODES * 256u;
constexpr float L2E = 1.4426950408889634f;
constexpr float RSCALE = 17.906f;
constexpr float RANGE_MAX = 61.0f;

__device__ unsigned int g_ticket;
__device__ __align__(128) unsigned long long g_flag[NB];
__device__ __align__(128) uint4 g_seg[(size_t)NB * NB * UMAIN];
__device__ __align__(128) uint4 g_tail[(size_t)NB * NB * UTAIL];
__device__ __align__(256) uint4 g_tab[(size_t)(N_NODES + 1) * 16];
__device__ float2 g_acc[(size_t)NB * NPB * 64];

#define PROFE() do {} while (0)
#define PROF(i) do {} while (0)
#define PROFG(i) do {} while (0)

__device__ __forceinline__ void cp_async16(uint32_t dst, const void* src) {
    asm volatile("cp.async.cg.shared.global [%0], [%1], 16;" :: "r"(dst), "l"(src) : "memory");
}
__device__ __forceinline__ void cp_async16_zfill(uint32_t dst, const void* src, int sz) {
    asm volatile("cp.async.cg.shared.global [%0], [%1], 16, %2;" :: "r"(dst), "l"(src), "r"(sz) : "memory");
}
__device__ __forceinline__ void cp_commit() { asm volatile("cp.async.commit_group;" ::: "memory"); }
template <int N> __device__ __forceinline__ void cp_wait() { asm volatile("cp.async.wait_group %0;" :: "n"(N) : "memory"); }
__device__ __forceinline__ void fence_async() { asm volatile("fence.proxy.async.shared::cta;" ::: "memory"); }
__device__ __forceinline__ void wgmma_fence() { asm volatile("wgmma.fence.sync.aligned;" ::: "memory"); }
__device__ __forceinline__ void wgmma_commit() { asm volatile("wgmma.commit_group.sync.aligned;" ::: "memory"); }
template <int N> __device__ __forceinline__ void wgmma_wait() { asm volatile("wgmma.wait_group.sync.aligned %0;" :: "n"(N) : "memory"); }
__device__ __forceinline__ void bar_sync(int id, int n) { asm volatile("bar.sync %0, %1;" :: "r"(id), "r"(n) : "memory"); }
__device__ __forceinline__ void bar_arrive(int id, int n) { asm volatile("bar.arrive %0, %1;" :: "r"(id), "r"(n) : "memory"); }
__device__ __forceinline__ int uni(int v) { return __shfl_sync(0xffffffffu, v, 0); }

__device__ __forceinline__ void ldsm_x4_t(uint32_t (&r)[4], uint32_t addr) {
    asm volatile("ldmatrix.sync.aligned.m8n8.x4.trans.shared.b16 {%0,%1,%2,%3}, [%4];"
                 : "=r"(r[0]), "=r"(r[1]), "=r"(r[2]), "=r"(r[3]) : "r"(addr) : "memory");
}
__device__ __forceinline__ void stsm_x4_t(uint32_t addr, uint32_t r0, uint32_t r1, uint32_t r2, uint32_t r3) {
    asm volatile("stmatrix.sync.aligned.m8n8.x4.trans.shared.b16 [%0], {%1,%2,%3,%4};"
                 :: "r"(addr), "r"(r0), "r"(r1), "r"(r2), "r"(r3) : "memory");
}
__device__ __forceinline__ uint32_t movm(uint32_t a) {
    uint32_t d; asm volatile("movmatrix.sync.aligned.m8n8.trans.b16 %0, %1;" : "=r"(d) : "r"(a)); return d;
}
__device__ __forceinline__ uint32_t lds32(uint32_t addr) {
    uint32_t v; asm volatile("ld.shared.u32 %0, [%1];" : "=r"(v) : "r"(addr) : "memory"); return v;
}
__device__ __forceinline__ uint2 lds64(uint32_t addr) {
    uint2 v; asm volatile("ld.shared.v2.u32 {%0,%1}, [%2];" : "=r"(v.x), "=r"(v.y) : "r"(addr) : "memory"); return v;
}
__device__ __forceinline__ uint4 lds128(uint32_t addr) {
    uint4 v; asm volatile("ld.shared.v4.u32 {%0,%1,%2,%3}, [%4];" : "=r"(v.x), "=r"(v.y), "=r"(v.z), "=r"(v.w) : "r"(addr) : "memory"); return v;
}
__device__ __forceinline__ void sts64(uint32_t addr, uint32_t a, uint32_t b) {
    asm volatile("st.shared.v2.u32 [%0], {%1,%2};" :: "r"(addr), "r"(a), "r"(b) : "memory");
}
__device__ __forceinline__ void sts128(uint32_t addr, uint32_t a, uint32_t b, uint32_t c, uint32_t d) {
    asm volatile("st.shared.v4.u32 [%0], {%1,%2,%3,%4};" :: "r"(addr), "r"(a), "r"(b), "r"(c), "r"(d) : "memory");
}
__device__ __forceinline__ void ldg128(uint32_t* r, const char* p) {
    asm volatile("ld.global.v4.u32 {%0,%1,%2,%3}, [%4];" : "=r"(r[0]), "=r"(r[1]), "=r"(r[2]), "=r"(r[3]) : "l"(p) : "memory");
}
__device__ __forceinline__ void ldg64_stream(uint32_t& a, uint32_t& b, const char* p) {
    asm volatile("ld.global.nc.L1::no_allocate.v2.u32 {%0,%1}, [%2];" : "=r"(a), "=r"(b) : "l"(p) : "memory");
}

__device__ __forceinline__ void mma_k16(float* d, uint32_t a0, uint32_t a1, uint32_t a2, uint32_t a3, uint32_t b0, uint32_t b1,
                                        float c0, float c1, float c2, float c3) {
    asm volatile("mma.sync.aligned.m16n8k16.row.col.f32.bf16.bf16.f32 {%0,%1,%2,%3}, {%4,%5,%6,%7}, {%8,%9}, {%10,%11,%12,%13};"
                 : "=f"(d[0]), "=f"(d[1]), "=f"(d[2]), "=f"(d[3])
                 : "r"(a0), "r"(a1), "r"(a2), "r"(a3), "r"(b0), "r"(b1), "f"(c0), "f"(c1), "f"(c2), "f"(c3));
}
__device__ __forceinline__ uint64_t desc_sw128(uint32_t saddr) {
    return (uint64_t)((saddr & 0x3FFFF) >> 4) | (1ull << 16) | (64ull << 32) | (1ull << 62);
}
template <int SCALE_D>
__device__ __forceinline__ void wgmma_n80(float (&d)[40], uint64_t da, uint64_t db) {
    asm volatile(
        "wgmma.mma_async.sync.aligned.m64n80k16.f32.bf16.bf16 "
        "{%0,%1,%2,%3,%4,%5,%6,%7,%8,%9,%10,%11,%12,%13,%14,%15,"
        "%16,%17,%18,%19,%20,%21,%22,%23,%24,%25,%26,%27,%28,%29,%30,%31,"
        "%32,%33,%34,%35,%36,%37,%38,%39}, "
        "%40, %41, %42, 1, 1, 1, 0;"
        : "+f"(d[0]), "+f"(d[1]), "+f"(d[2]), "+f"(d[3]), "+f"(d[4]), "+f"(d[5]), "+f"(d[6]), "+f"(d[7]),
          "+f"(d[8]), "+f"(d[9]), "+f"(d[10]), "+f"(d[11]), "+f"(d[12]), "+f"(d[13]), "+f"(d[14]), "+f"(d[15]),
          "+f"(d[16]), "+f"(d[17]), "+f"(d[18]), "+f"(d[19]), "+f"(d[20]), "+f"(d[21]), "+f"(d[22]), "+f"(d[23]),
          "+f"(d[24]), "+f"(d[25]), "+f"(d[26]), "+f"(d[27]), "+f"(d[28]), "+f"(d[29]), "+f"(d[30]), "+f"(d[31]),
          "+f"(d[32]), "+f"(d[33]), "+f"(d[34]), "+f"(d[35]), "+f"(d[36]), "+f"(d[37]), "+f"(d[38]), "+f"(d[39])
        : "l"(da), "l"(db), "n"(SCALE_D));
}
__device__ __forceinline__ void node_gemm(float (&d)[40], uint32_t wa, uint32_t xa) {
    const uint64_t da = desc_sw128(wa), db = desc_sw128(xa);
    wgmma_n80<0>(d, da, db);
    wgmma_n80<1>(d, da + 128, db + 2);
    wgmma_n80<1>(d, da + 256, db + 4);
    wgmma_n80<1>(d, da + 384, db + 6);
}
template <int NREG>
__device__ __forceinline__ void reg_fence(float (&d)[NREG]) {
    #pragma unroll
    for (int i = 0; i < NREG; i++) asm volatile("" : "+f"(d[i]) :: "memory");
}

__device__ __forceinline__ uint32_t pack_bf16(float lo, float hi) {
    uint32_t d; asm("cvt.rn.bf16x2.f32 %0, %1, %2;" : "=r"(d) : "f"(hi), "f"(lo)); return d;
}
__device__ __forceinline__ uint32_t fma_bf2(uint32_t a, uint32_t b, uint32_t c) {
    uint32_t d; asm("fma.rn.bf16x2 %0, %1, %2, %3;" : "=r"(d) : "r"(a), "r"(b), "r"(c)); return d;
}
__device__ __forceinline__ uint32_t add_bf2(uint32_t a, uint32_t b) {
    uint32_t d; asm("add.rn.bf16x2 %0, %1, %2;" : "=r"(d) : "r"(a), "r"(b)); return d;
}
__device__ __forceinline__ float ex2f(float x) {
    float y; asm("ex2.approx.ftz.f32 %0, %1;" : "=f"(y) : "f"(x)); return y;
}
__device__ __forceinline__ uint32_t fma_relu_bf2(uint32_t a, uint32_t b, uint32_t c) {
    uint32_t d; asm("fma.rn.relu.bf16x2 %0, %1, %2, %3;" : "=r"(d) : "r"(a), "r"(b), "r"(c)); return d;
}
__device__ __forceinline__ uint32_t gate_pair(float y0, float y1, uint32_t neb, uint32_t niea) {
    const uint32_t na = fma_bf2(pack_bf16(ex2f(y0), ex2f(y1)), neb, niea);
    const uint32_t r0 = ~na;
    const uint32_t e  = fma_relu_bf2(na, r0, 0x40EF40EFu);
    return fma_bf2(r0, e, r0);
}

__device__ __forceinline__ uint4 ld_relaxed_128(const uint4* p) {
    uint4 v;
    asm volatile("{\n\t.reg .b128 t;\n\tld.relaxed.gpu.global.b128 t, [%4];\n\tmov.b128 {%0,%1,%2,%3}, t;\n\t}"
                 : "=r"(v.x), "=r"(v.y), "=r"(v.z), "=r"(v.w) : "l"(p) : "memory");
    return v;
}
__device__ __forceinline__ void st_relaxed_128(uint4* p, uint4 v) {
    asm volatile("{\n\t.reg .b128 t;\n\tmov.b128 t, {%1,%2,%3,%4};\n\tst.relaxed.gpu.global.b128 [%0], t;\n\t}"
                 :: "l"(p), "r"(v.x), "r"(v.y), "r"(v.z), "r"(v.w) : "memory");
}
__device__ __forceinline__ void sts32(uint32_t addr, uint32_t a) { asm volatile("st.shared.u32 [%0], %1;" :: "r"(addr), "r"(a) : "memory"); }
__device__ __forceinline__ uint32_t atoms_inc_if(uint32_t addr, bool p, uint32_t dflt) {
    uint32_t r = dflt;
    asm volatile("{\n\t.reg .pred p;\n\tsetp.ne.u32 p, %2, 0;\n\t@p atom.shared.add.u32 %0, [%1], 1;\n\t}"
                 : "+r"(r) : "r"(addr), "r"((uint32_t)p) : "memory");
    return r;
}
__device__ __forceinline__ void sts64_if(uint32_t addr, uint32_t a, uint32_t b, bool p) {
    asm volatile("{\n\t.reg .pred p;\n\tsetp.ne.u32 p, %3, 0;\n\t@p st.shared.v2.u32 [%0], {%1,%2};\n\t}"
                 :: "r"(addr), "r"(a), "r"(b), "r"((uint32_t)p) : "memory");
}

__global__ void __launch_bounds__(NTHREADS, 1)
gatedgcn_kernel(const __nv_bfloat16* __restrict__ x, const __nv_bfloat16* __restrict__ e_attr,
                const int* __restrict__ src, const int* __restrict__ dst,
                const __nv_bfloat16* __restrict__ w_a, const __nv_bfloat16* __restrict__ w_b,
                const __nv_bfloat16* __restrict__ w_c, const __nv_bfloat16* __restrict__ w_u,
                const __nv_bfloat16* __restrict__ w_v, __nv_bfloat16* __restrict__ out) {
    extern __shared__ __align__(1024) unsigned char smem[];
    const uint32_t sb = (uint32_t)__cvta_generic_to_shared(smem);
    const int tid = threadIdx.x, lane = tid & 31;
    const int warp = uni(tid >> 5);
    const int cta = blockIdx.x;
    const int node0 = cta * NPB;
    const int g = lane >> 2, q = lane & 3;

    int* s_cnt  = (int*)(smem + SM_CNT);
    int* s_ncnt = (int*)(smem + SM_NCNT);
    volatile int* s_misc = (volatile int*)(smem + SM_MISC);

    auto load_weights = [&](int t, int nt) {
        #pragma unroll 1
        for (int i = t; i < 512; i += nt) {
            const uint32_t so = sb + SM_W + (i >> 3) * 128 + (((i ^ (i >> 3)) & 7) << 4);
            cp_async16(so + WS_B, w_b + i * 8);
            cp_async16(so + WS_V, w_v + i * 8);
            cp_async16(so + WS_A, w_a + i * 8);
            cp_async16(so + WS_U, w_u + i * 8);
        }
        if (t < 128) cp_async16(sb + SM_W + WS_C + (t >> 3) * 128 + (((t ^ (t >> 3)) & 7) << 4), w_c + t * 8);
    };

    auto store_rows = [&](const float (&d)[40], uint32_t base, int ld) {
        base += ((lane & 7) + ((lane >> 4) << 3)) * ld + ((warp & 3) * 16 + ((lane >> 3) & 1) * 8) * 2;
        #pragma unroll
        for (int w = 0; w < 10; w += 2)
            stsm_x4_t(base + w * 8 * ld,
                      pack_bf16(d[4 * w + 0], d[4 * w + 1]), pack_bf16(d[4 * w + 2], d[4 * w + 3]),
                      pack_bf16(d[4 * w + 4], d[4 * w + 5]), pack_bf16(d[4 * w + 6], d[4 * w + 7]));
    };
    auto neg_exp = [&](float (&d)[40], float scale, int slot) {
        float mx = 0.f;
        #pragma unroll
        for (int i = 0; i < 40; i++) { mx = fmaxf(mx, fabsf(d[i])); d[i] = -ex2f(d[i] * scale); }
        const uint32_t mb = __reduce_max_sync(0xffffffffu, __float_as_uint(mx));
        if (lane == 0) atomicMax((unsigned int*)&s_misc[slot], mb);
    };

    PROF(0);
    if (warp < NET / 32) {
        const int ebase = cta * CHUNK;
        const int nvec = (min(CHUNK, N_EDGES - ebase)) >> 2;
        int4 dv[4], sv[4];
        #pragma unroll
        for (int k = 0; k < 4; k++) {
            const int v = tid + k * NET;
            if (v < nvec) {
                dv[k] = __ldg((const int4*)(dst + ebase) + v);
                sv[k] = __ldg((const int4*)(src + ebase) + v);
            }
        }
        if (tid < 136 + 80 + 5 && tid != 136 + 80) s_cnt[tid] = 0;
        bar_sync(1, NET);
        PROF(1);

        #pragma unroll
        for (int k = 0; k < 4; k++) {
            const int v = tid + k * NET;
            if (v < nvec) {
                const int dd[4] = {dv[k].x, dv[k].y, dv[k].z, dv[k].w};
                const int ss[4] = {sv[k].x, sv[k].y, sv[k].z, sv[k].w};
                uint32_t b[4], rank[4];
                #pragma unroll
                for (int j = 0; j < 4; j++) { b[j] = (uint32_t)dd[j] / NPB; rank[j] = (uint32_t)atomicAdd(&s_cnt[b[j]], 1); }
                #pragma unroll
                for (int j = 0; j < 4; j++) {
                    const uint32_t rec = (((uint32_t)(v * 4 + j) - b[j]) * NPB + (uint32_t)dd[j]) * N_NODES + (uint32_t)ss[j];
                    sts32(sb + SM_STAGE + (b[j] * SEG_LD + min(rank[j], (uint32_t)SEGCAP)) * 4, rec);
                }
            }
        }
        const int sg = tid / UMAIN, su = tid - sg * UMAIN;
        const bool act = sg < SPP, act_last = sg + (UPT - 1) * SPP < NB;
        bar_sync(8, NET + 32);
        PROF(2);
        const uint32_t tag = (((uint32_t)s_misc[0] + 1u) & 0xFFFFFFu) << 8;
        if (act) {
            uint4 pu[UPT];
            uint32_t tmask = 0;
            const uint32_t a = sb + SM_STAGE + (sg * SEG_LD + 3 * su) * 4;
            #pragma unroll
            for (int k = 0; k < UPT; k++) {
                const int cnt = s_cnt[sg + k * SPP];
                pu[k].x = lds32(a + k * SPP * SEG_LD * 4); pu[k].y = lds32(a + k * SPP * SEG_LD * 4 + 4); pu[k].z = lds32(a + k * SPP * SEG_LD * 4 + 8);
                const int extra = min(max(cnt - 3 * UMAIN, 0), 31);
                pu[k].w = tag | (uint32_t)extra << 2 | (uint32_t)min(max(cnt - 3 * su, 0), 3);
                if (extra > 0) tmask |= 1u << k;
            }
            uint4* gq = g_seg + ((size_t)sg * NB + cta) * UMAIN + su;
            #pragma unroll
            for (int k = 0; k < UPT; k++)
                if (k < UPT - 1 || act_last) st_relaxed_128(gq + (size_t)k * SPP * NB * UMAIN, pu[k]);
            if (su >= UTAIL) tmask = 0;
            while (tmask) {
                const int b = sg + (__ffs(tmask) - 1) * SPP;
                tmask &= tmask - 1;
                const uint32_t ta = sb + SM_STAGE + (b * SEG_LD + 3 * (UMAIN + su)) * 4;
                st_relaxed_128(g_tail + ((size_t)b * NB + cta) * UTAIL + su, make_uint4(lds32(ta), lds32(ta + 4), lds32(ta + 8), tag));
            }
        }
        PROF(3);
        bar_sync(3, NTHREADS);
        if (warp < 8) {
            float d[40];
            wgmma_fence();
            node_gemm(d, sb + SM_W + (warp < 4 ? WS_A : WS_U), sb + SM_XOWN);
            wgmma_commit();
            wgmma_wait<0>();
            reg_fence(d);
            if (warp < 4) neg_exp(d, L2E, 4);
            store_rows(d, sb + (warp < 4 ? SM_IEA : SM_U), U_LD);
        } else {
            #pragma unroll
            for (int k = 0; k < 4; k++) {
                const int i = tid - 256 + k * 128;
                const int l = i >> 4, j = (i >> 1) & 7, h = i & 1;
                const int f = 32 * (j >> 2) + 8 * (l >> 3) + 2 * (j & 3) + ((l >> 2) & 1);
                const int r = 4 * (l & 3) + 2 * h;
                const unsigned char* wc = smem + SM_W + WS_C + (f & 7) * 2;
                const float c0 = __bfloat162float(*(const __nv_bfloat16*)(wc + r * 128 + (((f >> 3) ^ (r & 7)) << 4)));
                const float c1 = __bfloat162float(*(const __nv_bfloat16*)(wc + (r + 1) * 128 + (((f >> 3) ^ ((r + 1) & 7)) << 4)));
                ((uint32_t*)(smem + SM_WCF))[((i >> 2) & 3) * 128 + l * 4 + (i & 3)] = pack_bf16(c0 * -L2E, c1 * -L2E);
            }
        }
        #pragma unroll 4
        for (int i = tid; i < NULLT / 16; i += NET) sts128(sb + SM_LIST + i * 16, NULL_W0, 0u, NULL_W0, 0u);
        PROF(15);
        const uint4* gp = g_seg + (size_t)cta * NB * UMAIN + tid;
        uint4 rec[UPT];
        #pragma unroll
        for (int k = 0; k < UPT; k++) {
            rec[k].w = tag;
            if (k < UPT - 1 ? act : act_last) rec[k] = ld_relaxed_128(gp + k * SPP * UMAIN);
        }
        bar_sync(1, NET);
        PROF(4);
        {
            uint32_t tmask = 0, pend = (1u << UPT) - 1;
            for (int tries = 0; pend; tries++) {
                #pragma unroll
                for (int k = 0; k < UPT; k++) {
                    if (pend >> k & 1) {
                        const bool ok = ((rec[k].w ^ tag) >> 8) == 0;
                        if (__all_sync(0xffffffffu, ok)) {
                            pend &= ~(1u << k);
                            const uint32_t w[3] = {rec[k].x, rec[k].y, rec[k].z};
                            const int n = rec[k].w & 3;
                            uint32_t t[3], el[3], dl[3], r[3];
                            #pragma unroll
                            for (int j = 0; j < 3; j++) {
                                t[j] = w[j] / N_NODES;
                                el[j] = t[j] / NPB;
                                dl[j] = t[j] - el[j] * NPB;
                                r[j] = atoms_inc_if(sb + SM_NCNT + dl[j] * 4, j < n, 0u);
                            }
                            #pragma unroll
                            for (int j = 0; j < 3; j++)
                                sts64_if(sb + SM_LIST + dl[j] * LIST_LD + min(r[j], (uint32_t)CAPN) * 8,
                                         (w[j] - t[j] * N_NODES) << 8, ((sg + k * SPP) * CHUNK + el[j]) * 32u, j < n);
                            if (rec[k].w & 0x7C) tmask |= 1u << k;
                        } else if (!ok) rec[k] = ld_relaxed_128(gp + k * SPP * UMAIN);
                    }
                }
                if (tries > 400000) { s_misc[1] = 1; break; }
            }
            if (su >= UTAIL) tmask = 0;
            while (tmask) {
                const int k = __ffs(tmask) - 1;
                tmask &= tmask - 1;
                const int pr = sg + k * SPP;
                const int extra = (ld_relaxed_128(gp + k * SPP * UMAIN).w >> 2) & 31;
                uint4 v;
                int tries = 0;
                do { v = ld_relaxed_128(g_tail + ((size_t)cta * NB + pr) * UTAIL + su); } while (v.w != tag && ++tries < 400000);
                if (v.w != tag || extra > 3 * UTAIL) s_misc[1] = 1;
                else {
                    const uint32_t w[3] = {v.x, v.y, v.z};
                    #pragma unroll 1
                    for (int j = 0; j < 3; j++) {
                        if (3 * su + j < extra) {
                            const uint32_t ww = j == 0 ? w[0] : j == 1 ? w[1] : w[2];
                            const uint32_t t = ww / N_NODES, e = t / NPB, dl = t - e * NPB;
                            const uint32_t rr = (uint32_t)atomicAdd(&s_ncnt[dl], 1);
                            sts64(sb + SM_LIST + dl * LIST_LD + min(rr, (uint32_t)CAPN) * 8, (ww - t * N_NODES) << 8, (pr * CHUNK + e) * 32u);
                        }
                    }
                }
            }
        }
        PROF(5);
    } else {
        const int wtid = tid - NET;
        {
            const uint32_t so = (wtid >> 3) * 128 + (((wtid ^ (wtid >> 3)) & 7) << 4);
            #pragma unroll
            for (int k = 0; k < 5; k++) {
                const int r = (wtid >> 3) + 16 * k;
                const bool ok = r < NPB && node0 + r < N_NODES;
                cp_async16_zfill(sb + SM_XOWN + so + k * 2048, x + (ok ? (size_t)node0 * 64 + wtid * 8 + k * 1024 : 0), ok ? 16 : 0);
            }
            #pragma unroll
            for (int k = 0; k < 4; k++) {
                cp_async16(sb + SM_W + WS_V + so + k * 2048, w_v + wtid * 8 + k * 1024);
                cp_async16(sb + SM_W + WS_B + so + k * 2048, w_b + wtid * 8 + k * 1024);
            }
            cp_commit();
            #pragma unroll
            for (int k = 0; k < 4; k++) {
                cp_async16(sb + SM_W + WS_A + so + k * 2048, w_a + wtid * 8 + k * 1024);
                cp_async16(sb + SM_W + WS_U + so + k * 2048, w_u + wtid * 8 + k * 1024);
            }
            cp_async16(sb + SM_W + WS_C + so, w_c + wtid * 8);
            cp_commit();
        }
        if (wtid >= 96) {
            if (lane == 0) {
                uint32_t ticket;
                asm volatile("atom.relaxed.gpu.global.inc.u32 %0, [%1], %2;" : "=r"(ticket) : "l"(&g_ticket), "r"((uint32_t)NB * (1u << 24) - 1u) : "memory");
                s_misc[0] = (int)(ticket / NB);
            }
            __syncwarp();
            bar_arrive(8, NET + 32);
        }
        if (wtid < 8) sts128(sb + SM_LIST + NULLT + wtid * 16, NULL_W0, 0u, NULL_W0, 0u);
        if (wtid >= 8 && wtid < 11) s_misc[wtid - 3] = 0;
        cp_wait<1>();
        fence_async();
        bar_sync(2, 128);
        PROFG(10);
        {
            float db[40], dv[40];
            wgmma_fence();
            node_gemm(dv, sb + SM_W + WS_V, sb + SM_XOWN);
            wgmma_commit();
            node_gemm(db, sb + SM_W + WS_B, sb + SM_XOWN);
            wgmma_commit();
            wgmma_wait<1>();
            reg_fence(dv);
            store_rows(dv, sb + SM_T + 128, T_LD);
            wgmma_wait<0>();
            reg_fence(db);
            neg_exp(db, -L2E, 5);
            store_rows(db, sb + SM_T, T_LD);
        }
        bar_sync(2, 128);
        PROFG(11);
        {
            uint4 v[10];
            #pragma unroll
            for (int k = 0; k < 10; k++) v[k] = lds128(sb + SM_T + ((wtid >> 4) + 8 * k) * T_LD + (wtid & 15) * 16);
            #pragma unroll
            for (int k = 0; k < 10; k++) {
                const int r = (wtid >> 4) + 8 * k;
                if (node0 + r == N_NODES) v[k].x = v[k].y = v[k].z = v[k].w = (wtid & 8) ? 0u : 0xFF80FF80u;
                if (r < NPB && node0 + r <= N_NODES) g_tab[(size_t)node0 * 16 + wtid + k * 128] = v[k];
            }
        }
        cp_wait<0>();
        fence_async();
        bar_arrive(3, NTHREADS);
        bar_sync(2, 128);
        PROFG(12);
        if (wtid >= 96) {
            const uint32_t ftag = (uint32_t)s_misc[0] + 1u;
            if (lane == 0)
                asm volatile("st.release.gpu.global.u64 [%0], %1;"
                             :: "l"(&g_flag[cta]), "l"(((unsigned long long)ftag << 32) | (uint32_t)s_misc[5]) : "memory");
            __syncwarp();
            uint32_t mx;
            for (int tries = 0;; tries++) {
                __nanosleep(150);
                bool ok = true;
                mx = 0;
                #pragma unroll
                for (int k = 0; k < 3; k++) {
                    if (k < 2 || lane < NB / 2 - 64) {
                        const uint4 f = ld_relaxed_128((const uint4*)g_flag + lane + 32 * k);
                        ok = ok && f.y == ftag && f.w == ftag;
                        mx = max(mx, max(f.x, f.z));
                    }
                }
                if (__all_sync(0xffffffffu, ok)) break;
                if (tries > 100000) { mx = 0x7F800000u; break; }
            }
            asm volatile("fence.acq_rel.gpu;" ::: "memory");
            mx = __reduce_max_sync(0xffffffffu, mx);
            if (lane == 0) s_misc[6] = (int)mx;
        }
        PROFG(9);
    }
    __syncthreads();
    PROF(6);
    const bool bad_list = s_misc[1] != 0 ||
        __any_sync(0xffffffffu, max(max(s_ncnt[lane], s_ncnt[lane + 32]), s_ncnt[min(lane + 64, NPB - 1)]) > CAPN);

    auto reduce_rows = [&](float (&sum)[4], const uint32_t (&den)[8], const uint32_t (&num)[8]) {
        float s1[4] = {0.f, 0.f, 0.f, 0.f}, s2[4] = {0.f, 0.f, 0.f, 0.f};
        uint32_t ln;
        asm volatile("mov.u32 %0, %%laneid;" : "=r"(ln));
        #pragma unroll
        for (int j = 0; j < 4; j++) {
            const uint32_t sel = ((ln >> 2) & 3) == j ? 0x3F803F80u : 0u;
            mma_k16(s1, sel, 0u, 0u, sel, movm(den[j]), movm(num[j]), s1[0], s1[1], s1[2], s1[3]);
            mma_k16(s2, sel, 0u, 0u, sel, movm(den[j + 4]), movm(num[j + 4]), s2[0], s2[1], s2[2], s2[3]);
        }
        #pragma unroll
        for (int i = 0; i < 4; i++) sum[i] = ln < 16 ? s1[i] : s2[i];
    };
    auto write_node = [&](int node, const float (&sum)[4], int f0) {
        if (node0 + node < N_NODES) {
            const uint32_t iw = lds32(sb + SM_IEA + node * U_LD + f0 * 2);
            const uint32_t uw = lds32(sb + SM_U + node * U_LD + f0 * 2);
            const uint32_t xw = lds32(sb + SM_XOWN + node * 128 + (((f0 >> 3) ^ (node & 7)) << 4) + (f0 & 7) * 2);
            const float i0 = __uint_as_float(iw << 16), i1 = __uint_as_float(iw & 0xFFFF0000u);
            const float z0 = __uint_as_float(uw << 16) + __fdividef(sum[2] * i0, sum[0] * i0 - RSCALE * 1e-6f);
            const float z1 = __uint_as_float(uw & 0xFFFF0000u) + __fdividef(sum[3] * i1, sum[1] * i1 - RSCALE * 1e-6f);
            const float o0 = __uint_as_float(xw << 16) + fmaxf(z0, 0.f);
            const float o1 = __uint_as_float(xw & 0xFFFF0000u) + fmaxf(z1, 0.f);
            *(uint32_t*)(out + (size_t)(node0 + node) * 64 + f0) = pack_bf16(o0, o1);
        }
    };
    const char* eq = (const char*)e_attr + q * 8;
    const uint32_t la = sb + SM_LIST + g * 8;
    const bool fast = !bad_list && __int_as_float(s_misc[4]) + __int_as_float(s_misc[6]) <= RANGE_MAX;

    if (fast) {
        auto job_range = [&](int j, int& tb, int& te) {
            tb = NULLT; te = NULLT + 128;
            if (j >= NPB) return -1;
            tb = j * LIST_LD; te = tb + max(1, (s_ncnt[j] + 15) >> 4) * 128;
            return j;
        };
        const char* tabq = (const char*)g_tab + q * 16;
        asm volatile("" : "+l"(tabq));
        uint32_t wcf[16];
        #pragma unroll
        for (int i = 0; i < 4; i++) {
            const uint4 v = lds128(sb + SM_WCF + i * 512 + lane * 16);
            wcf[4 * i] = v.x; wcf[4 * i + 1] = v.y; wcf[4 * i + 2] = v.z; wcf[4 * i + 3] = v.w;
        }
        uint32_t eb[2][8], hq[2][8], ev[4];
        const char *p0, *p1;
        bool v0, v1;
        auto load_rec = [&](int tt) {
            const uint2 r0 = lds64(la + tt), r1 = lds64(la + tt + 64);
            p0 = tabq + r0.x; p1 = tabq + r1.x;
            v0 = r0.x != NULL_W0; v1 = r1.x != NULL_W0;
            ldg64_stream(ev[0], ev[2], eq + r0.y);
            ldg64_stream(ev[1], ev[3], eq + r1.y);
        };
        auto load_rows = [&]() {
            ldg128(&eb[0][0], p0); ldg128(&eb[0][4], p0 + 64); ldg128(&eb[1][0], p1); ldg128(&eb[1][4], p1 + 64);
            ldg128(&hq[0][0], p0 + 128); ldg128(&hq[0][4], p0 + 192); ldg128(&hq[1][0], p1 + 128); ldg128(&hq[1][4], p1 + 192);
        };
        int t, te;
        int node = job_range(warp, t, te);
        load_rec(t);
        load_rows();
        while (true) {
            int ntb, nte;
            const int nnode = job_range(uni((int)atoms_inc_if(sb + SM_MISC + 12, lane == 0, 0u)) + NWARPS, ntb, nte);
            uint32_t iea[8], den[8], num[8];
            {
                const uint4 w0 = lds128(sb + SM_IEA + node * U_LD + q * 16), w1 = lds128(sb + SM_IEA + node * U_LD + 64 + q * 16);
                iea[0] = w0.x; iea[1] = w0.y; iea[2] = w0.z; iea[3] = w0.w; iea[4] = w1.x; iea[5] = w1.y; iea[6] = w1.z; iea[7] = w1.w;
            }
            #pragma unroll
            for (int j = 0; j < 8; j++) { den[j] = 0u; num[j] = 0u; }
            bool last;
            do {
                const uint32_t a0 = v0 ? ev[0] : 0u, a1 = v1 ? ev[1] : 0u, a2 = v0 ? ev[2] : 0u, a3 = v1 ? ev[3] : 0u;
                t += 128;
                last = t == te;
                load_rec(last ? ntb : t);
                #pragma unroll
                for (int h = 0; h < 2; h++) {
                    float d[16];
                    #pragma unroll
                    for (int j = 0; j < 4; j++)
                        mma_k16(&d[4 * j], a0, a1, a2, a3, wcf[8 * h + 2 * j], wcf[8 * h + 2 * j + 1], 0.f, 0.f, 0.f, 0.f);
                    #pragma unroll
                    for (int jj = 0; jj < 4; jj++) {
                        const int j = 4 * h + jj;
                        const uint32_t ra = gate_pair(d[4 * jj], d[4 * jj + 1], eb[0][j], iea[j]);
                        const uint32_t rb = gate_pair(d[4 * jj + 2], d[4 * jj + 3], eb[1][j], iea[j]);
                        den[j] = add_bf2(add_bf2(den[j], ra), rb);
                        num[j] = fma_bf2(rb, hq[1][j], fma_bf2(ra, hq[0][j], num[j]));
                    }
                }
                load_rows();
            } while (!last);
            const int f0 = 32 * (g >> 2) + 8 * q + 2 * (g & 3);
            float sum[4];
            reduce_rows(sum, den, num);
            write_node(node, sum, f0);
            if (nnode < 0) break;
            node = nnode; t = ntb; te = nte;
        }
        PROFE();
    } else {
        float2* acc = g_acc + (size_t)cta * NPB * 64;
        __syncthreads();
        load_weights(tid, NTHREADS);
        cp_commit();
        for (int i = tid; i < NPB * 64; i += NTHREADS) acc[i] = make_float2(0.f, 0.f);
        cp_wait<0>();
        int scan_pos = bad_list ? 0 : N_EDGES;
        int pend = 0, pv = 0;
        int4 d4 = make_int4(0, 0, 0, 0);
        bool more = true;
        while (more) {
            if (bad_list) {
                __syncthreads();
                if (tid < 80) s_ncnt[tid] = 0;
                __syncthreads();
                while (true) {
                    const int dd[4] = {d4.x, d4.y, d4.z, d4.w};
                    #pragma unroll
                    for (int j = 0; j < 4; j++) {
                        if (pend >> j & 1) {
                            const int dl = dd[j] - node0;
                            const int r = atomicAdd(&s_ncnt[dl], 1);
                            if (r < CAPN) {
                                const int e = pv * 4 + j;
                                sts64(sb + SM_LIST + dl * LIST_LD + r * 8, (uint32_t)__ldg(src + e) << 8, (uint32_t)e * 32u);
                                pend &= ~(1 << j);
                            }
                        }
                    }
                    if (__syncthreads_or(pend)) break;
                    if (scan_pos >= N_EDGES) { more = false; break; }
                    pv = (scan_pos >> 2) + tid;
                    if (pv < N_EDGES / 4) {
                        d4 = __ldg((const int4*)dst + pv);
                        pend = ((uint32_t)(d4.x - node0) < NPB ? 1 : 0) | ((uint32_t)(d4.y - node0) < NPB ? 2 : 0)
                             | ((uint32_t)(d4.z - node0) < NPB ? 4 : 0) | ((uint32_t)(d4.w - node0) < NPB ? 8 : 0);
                    }
                    scan_pos += NTHREADS * 4;
                }
            } else {
                more = false;
                __syncthreads();
            }
            const uint32_t wrow = sb + SM_W + (lane & 15) * 128;
            #pragma unroll 1
            for (int job = warp; job < NPB * 4; job += NWARPS) {
                const int n = job >> 2, jp = job & 3;
                const int cnt = min(s_ncnt[n], CAPN);
                if (cnt == 0) continue;
                const uint32_t wa = wrow + (((2 * jp + (lane >> 4)) ^ (lane & 7)) << 4);
                float ca[8] = {0.f, 0.f, 0.f, 0.f, 0.f, 0.f, 0.f, 0.f};
                #pragma unroll
                for (int k = 0; k < 4; k++) {
                    const uint32_t a0 = lds32(sb + SM_XOWN + n * 128 + (((2 * k) ^ (n & 7)) << 4) + q * 4);
                    const uint32_t a2 = lds32(sb + SM_XOWN + n * 128 + (((2 * k + 1) ^ (n & 7)) << 4) + q * 4);
                    uint32_t b[4];
                    ldsm_x4_t(b, wa + WS_A + k * 2048);
                    mma_k16(&ca[0], a0, a0, a2, a2, b[0], b[1], ca[0], ca[1], ca[2], ca[3]);
                    mma_k16(&ca[4], a0, a0, a2, a2, b[2], b[3], ca[4], ca[5], ca[6], ca[7]);
                }
                float sd[4] = {0.f, 0.f, 0.f, 0.f}, sn[4] = {0.f, 0.f, 0.f, 0.f};
                #pragma unroll 1
                for (int i0 = 0; i0 < cnt; i0 += 16) {
                    const bool v0 = i0 + g < cnt, v1 = i0 + g + 8 < cnt;
                    const uint2 r0 = lds64(sb + SM_LIST + n * LIST_LD + (v0 ? i0 + g : 0) * 8);
                    const uint2 r1 = lds64(sb + SM_LIST + n * LIST_LD + (v1 ? i0 + g + 8 : 0) * 8);
                    const uint32_t* x0 = (const uint32_t*)((const char*)x + (r0.x >> 1)) + q;
                    const uint32_t* x1 = (const uint32_t*)((const char*)x + (r1.x >> 1)) + q;
                    const uint32_t* e0 = (const uint32_t*)((const char*)e_attr + r0.y) + q;
                    const uint32_t* e1 = (const uint32_t*)((const char*)e_attr + r1.y) + q;
                    float gg[8], hh[8] = {0.f, 0.f, 0.f, 0.f, 0.f, 0.f, 0.f, 0.f};
                    uint32_t b[4];
                    {
                        const uint32_t a0 = __ldg(e0), a1 = __ldg(e1), a2 = __ldg(e0 + 4), a3 = __ldg(e1 + 4);
                        ldsm_x4_t(b, wa + WS_C);
                        mma_k16(&gg[0], a0, a1, a2, a3, b[0], b[1], ca[0], ca[1], ca[2], ca[3]);
                        mma_k16(&gg[4], a0, a1, a2, a3, b[2], b[3], ca[4], ca[5], ca[6], ca[7]);
                    }
                    #pragma unroll
                    for (int k = 0; k < 4; k++) {
                        const uint32_t a0 = __ldg(x0 + 8 * k), a1 = __ldg(x1 + 8 * k), a2 = __ldg(x0 + 8 * k + 4), a3 = __ldg(x1 + 8 * k + 4);
                        ldsm_x4_t(b, wa + WS_B + k * 2048);
                        mma_k16(&gg[0], a0, a1, a2, a3, b[0], b[1], gg[0], gg[1], gg[2], gg[3]);
                        mma_k16(&gg[4], a0, a1, a2, a3, b[2], b[3], gg[4], gg[5], gg[6], gg[7]);
                        ldsm_x4_t(b, wa + WS_V + k * 2048);
                        mma_k16(&hh[0], a0, a1, a2, a3, b[0], b[1], hh[0], hh[1], hh[2], hh[3]);
                        mma_k16(&hh[4], a0, a1, a2, a3, b[2], b[3], hh[4], hh[5], hh[6], hh[7]);
                    }
                    #pragma unroll
                    for (int i = 0; i < 8; i++) {
                        const float eta = ((i & 2) ? v1 : v0) ? 1.0f / (1.0f + ex2f(gg[i] * -L2E)) : 0.f;
                        const int o = (i >> 2) * 2 + (i & 1);
                        sd[o] += eta;
                        sn[o] = fmaf(eta, hh[i], sn[o]);
                    }
                }
                #pragma unroll
                for (int i = 0; i < 4; i++) {
                    #pragma unroll
                    for (int o = 4; o < 32; o <<= 1) {
                        sd[i] += __shfl_xor_sync(0xffffffffu, sd[i], o);
                        sn[i] += __shfl_xor_sync(0xffffffffu, sn[i], o);
                    }
                }
                if (g == 0) {
                    #pragma unroll
                    for (int i = 0; i < 4; i++) {
                        float2* pa = acc + n * 64 + jp * 16 + (i >> 1) * 8 + 2 * q + (i & 1);
                        *pa = make_float2(pa->x + sd[i], pa->y + sn[i]);
                    }
                }
            }
        }
        __syncthreads();
        for (int i = tid; i < NPB * 64; i += NTHREADS) {
            const int n = i >> 6, f = i & 63;
            if (node0 + n < N_NODES) {
                const float2 a = acc[i];
                const float u = __bfloat162float(*(const __nv_bfloat16*)(smem + SM_U + n * U_LD + f * 2));
                const float xv = __bfloat162float(*(const __nv_bfloat16*)(smem + SM_XOWN + n * 128 + (((f >> 3) ^ (n & 7)) << 4) + (f & 7) * 2));
                out[(size_t)(node0 + n) * 64 + f] = __float2bfloat16(xv + fmaxf(u + a.y / (a.x + 1e-6f), 0.f));
            }
        }
    }
}

}

extern "C" void kernel_launch(void* const* d_in, const int* in_sizes, int n_in, void* d_out, int out_size) {
    (void)in_sizes; (void)n_in; (void)out_size;
    constexpr int SMEM = SM_TOTAL + 128;
    cudaFuncSetAttribute(gatedgcn_kernel, cudaFuncAttributeMaxDynamicSharedMemorySize, SMEM);
    gatedgcn_kernel<<<NB, NTHREADS, SMEM>>>(
        (const __nv_bfloat16*)d_in[0], (const __nv_bfloat16*)d_in[1], (const int*)d_in[2], (const int*)d_in[3],
        (const __nv_bfloat16*)d_in[4], (const __nv_bfloat16*)d_in[5], (const __nv_bfloat16*)d_in[6],
        (const __nv_bfloat16*)d_in[7], (const __nv_bfloat16*)d_in[8], (__nv_bfloat16*)d_out);
}
```

```cpp
#include <cuda_runtime.h>
#include <cuda_bf16.h>
#include <stdint.h>

namespace {

constexpr int N_NODES  = 10000;
constexpr int N_EDGES  = 640000;
constexpr int NB       = 132;
constexpr int NPB      = 76;
constexpr int CHUNK    = 4864;
constexpr int UMAIN    = 20;
constexpr int UTAIL    = 8;
constexpr int SEGCAP   = 3 * (UMAIN + UTAIL);
constexpr int SEG_LD   = SEGCAP + 1;
constexpr int CAPN     = 112;
constexpr int LIST_LD  = (CAPN + 1) * 8;
constexpr int NTHREADS = 512;
constexpr int NWARPS   = NTHREADS / 32;
constexpr int NET      = 384;
#define NSPLIT_ 12
constexpr int NSPLIT   = NSPLIT_;
constexpr int NWHOLE   = NPB - NSPLIT;
constexpr int NJOBS    = NWHOLE + 2 * NSPLIT;
constexpr int SPP      = NET / UMAIN;
constexpr int UPT      = (NB + SPP - 1) / SPP;
static_assert(NB * NPB > N_NODES && NB * CHUNK >= N_EDGES, "coverage");

constexpr int U_LD = 144;
constexpr int T_LD = 272;

constexpr int SM_XOWN  = 0;
constexpr int SM_LIST  = SM_XOWN + 80 * 128;
constexpr int SM_STAGE = SM_LIST;
constexpr int NULLT    = NPB * LIST_LD;
constexpr int SM_T     = SM_LIST + NULLT - 80 * T_LD;
constexpr int SM_W     = (SM_LIST + NULLT + 128 + 1023) / 1024 * 1024;
constexpr int W_BYTES  = (4 * 64 + 16) * 128;
constexpr int SM_IEA   = SM_W;
constexpr int SM_PART  = SM_W + 16384;
constexpr int SM_U     = SM_W + W_BYTES;
constexpr int SM_WCF   = SM_U + 80 * U_LD;
constexpr int SM_CNT   = SM_WCF + 2048;
constexpr int SM_NCNT  = SM_CNT + 136 * 4;
constexpr int SM_MISC  = SM_NCNT + 80 * 4;
constexpr int SM_STATE = SM_MISC + 8 * 4;
constexpr int SM_TOTAL = SM_STATE + 32 * 4;
static_assert(SM_STAGE + NB * SEG_LD * 4 <= SM_T && SM_T % 16 == 0, "staging fits");
static_assert(SM_W % 16 == 0 && NULLT % 16 == 0, "alignment");
static_assert((unsigned long long)CHUNK * NPB * N_NODES <= 0xFFFFFFFFull, "record fits 32 bits");
static_assert(80 * U_LD <= 16384 && NSPLIT <= 32, "aliases fit");
static_assert(SM_TOTAL <= 134144 - 256, "fits the 132 KB carve-out");

constexpr int WS_B = 0, WS_V = 8192, WS_A = 16384, WS_U = 24576, WS_C = 32768;

constexpr uint32_t NULL_W0 = (uint32_t)N_NODES * 256u;
constexpr float L2E = 1.4426950408889634f;
constexpr float RSCALE = 17.906f;
constexpr float RANGE_MAX = 61.0f;

__device__ unsigned int g_ticket;
__device__ __align__(128) unsigned long long g_flag[NB];
__device__ __align__(128) uint4 g_seg[(size_t)NB * NB * UMAIN];
__device__ __align__(128) uint4 g_tail[(size_t)NB * NB * UTAIL];
__device__ __align__(256) uint4 g_tab[(size_t)(N_NODES + 1) * 16];
__device__ float2 g_acc[(size_t)NB * NPB * 64];

#define PROFE() do {} while (0)
#define PROF(i) do {} while (0)
#define PROFG(i) do {} while (0)

__device__ __forceinline__ void cp_async16(uint32_t dst, const void* src) {
    asm volatile("cp.async.cg.shared.global [%0], [%1], 16;" :: "r"(dst), "l"(src) : "memory");
}
__device__ __forceinline__ void cp_async16_zfill(uint32_t dst, const void* src, int sz) {
    asm volatile("cp.async.cg.shared.global [%0], [%1], 16, %2;" :: "r"(dst), "l"(src), "r"(sz) : "memory");
}
__device__ __forceinline__ void cp_commit() { asm volatile("cp.async.commit_group;" ::: "memory"); }
template <int N> __device__ __forceinline__ void cp_wait() { asm volatile("cp.async.wait_group %0;" :: "n"(N) : "memory"); }
__device__ __forceinline__ void fence_async() { asm volatile("fence.proxy.async.shared::cta;" ::: "memory"); }
__device__ __forceinline__ void wgmma_fence() { asm volatile("wgmma.fence.sync.aligned;" ::: "memory"); }
__device__ __forceinline__ void wgmma_commit() { asm volatile("wgmma.commit_group.sync.aligned;" ::: "memory"); }
template <int N> __device__ __forceinline__ void wgmma_wait() { asm volatile("wgmma.wait_group.sync.aligned %0;" :: "n"(N) : "memory"); }
__device__ __forceinline__ void bar_sync(int id, int n) { asm volatile("bar.sync %0, %1;" :: "r"(id), "r"(n) : "memory"); }
__device__ __forceinline__ void bar_arrive(int id, int n) { asm volatile("bar.arrive %0, %1;" :: "r"(id), "r"(n) : "memory"); }
__device__ __forceinline__ int uni(int v) { return __shfl_sync(0xffffffffu, v, 0); }

__device__ __forceinline__ void ldsm_x4_t(uint32_t (&r)[4], uint32_t addr) {
    asm volatile("ldmatrix.sync.aligned.m8n8.x4.trans.shared.b16 {%0,%1,%2,%3}, [%4];"
                 : "=r"(r[0]), "=r"(r[1]), "=r"(r[2]), "=r"(r[3]) : "r"(addr) : "memory");
}
__device__ __forceinline__ void stsm_x4_t(uint32_t addr, uint32_t r0, uint32_t r1, uint32_t r2, uint32_t r3) {
    asm volatile("stmatrix.sync.aligned.m8n8.x4.trans.shared.b16 [%0], {%1,%2,%3,%4};"
                 :: "r"(addr), "r"(r0), "r"(r1), "r"(r2), "r"(r3) : "memory");
}
__device__ __forceinline__ uint32_t movm(uint32_t a) {
    uint32_t d; asm volatile("movmatrix.sync.aligned.m8n8.trans.b16 %0, %1;" : "=r"(d) : "r"(a)); return d;
}
__device__ __forceinline__ uint32_t lds32(uint32_t addr) {
    uint32_t v; asm volatile("ld.shared.u32 %0, [%1];" : "=r"(v) : "r"(addr) : "memory"); return v;
}
__device__ __forceinline__ uint2 lds64(uint32_t addr) {
    uint2 v; asm volatile("ld.shared.v2.u32 {%0,%1}, [%2];" : "=r"(v.x), "=r"(v.y) : "r"(addr) : "memory"); return v;
}
__device__ __forceinline__ uint4 lds128(uint32_t addr) {
    uint4 v; asm volatile("ld.shared.v4.u32 {%0,%1,%2,%3}, [%4];" : "=r"(v.x), "=r"(v.y), "=r"(v.z), "=r"(v.w) : "r"(addr) : "memory"); return v;
}
__device__ __forceinline__ void sts64(uint32_t addr, uint32_t a, uint32_t b) {
    asm volatile("st.shared.v2.u32 [%0], {%1,%2};" :: "r"(addr), "r"(a), "r"(b) : "memory");
}
__device__ __forceinline__ void sts128(uint32_t addr, uint32_t a, uint32_t b, uint32_t c, uint32_t d) {
    asm volatile("st.shared.v4.u32 [%0], {%1,%2,%3,%4};" :: "r"(addr), "r"(a), "r"(b), "r"(c), "r"(d) : "memory");
}
__device__ __forceinline__ void ldg128(uint32_t* r, const char* p) {
    asm volatile("ld.global.v4.u32 {%0,%1,%2,%3}, [%4];" : "=r"(r[0]), "=r"(r[1]), "=r"(r[2]), "=r"(r[3]) : "l"(p) : "memory");
}
__device__ __forceinline__ void ldg64_stream(uint32_t& a, uint32_t& b, const char* p) {
    asm volatile("ld.global.nc.L1::no_allocate.v2.u32 {%0,%1}, [%2];" : "=r"(a), "=r"(b) : "l"(p) : "memory");
}

__device__ __forceinline__ void mma_k16(float* d, uint32_t a0, uint32_t a1, uint32_t a2, uint32_t a3, uint32_t b0, uint32_t b1,
                                        float c0, float c1, float c2, float c3) {
    asm volatile("mma.sync.aligned.m16n8k16.row.col.f32.bf16.bf16.f32 {%0,%1,%2,%3}, {%4,%5,%6,%7}, {%8,%9}, {%10,%11,%12,%13};"
                 : "=f"(d[0]), "=f"(d[1]), "=f"(d[2]), "=f"(d[3])
                 : "r"(a0), "r"(a1), "r"(a2), "r"(a3), "r"(b0), "r"(b1), "f"(c0), "f"(c1), "f"(c2), "f"(c3));
}
__device__ __forceinline__ uint64_t desc_sw128(uint32_t saddr) {
    return (uint64_t)((saddr & 0x3FFFF) >> 4) | (1ull << 16) | (64ull << 32) | (1ull << 62);
}
template <int SCALE_D>
__device__ __forceinline__ void wgmma_n80(float (&d)[40], uint64_t da, uint64_t db) {
    asm volatile(
        "wgmma.mma_async.sync.aligned.m64n80k16.f32.bf16.bf16 "
        "{%0,%1,%2,%3,%4,%5,%6,%7,%8,%9,%10,%11,%12,%13,%14,%15,"
        "%16,%17,%18,%19,%20,%21,%22,%23,%24,%25,%26,%27,%28,%29,%30,%31,"
        "%32,%33,%34,%35,%36,%37,%38,%39}, "
        "%40, %41, %42, 1, 1, 1, 0;"
        : "+f"(d[0]), "+f"(d[1]), "+f"(d[2]), "+f"(d[3]), "+f"(d[4]), "+f"(d[5]), "+f"(d[6]), "+f"(d[7]),
          "+f"(d[8]), "+f"(d[9]), "+f"(d[10]), "+f"(d[11]), "+f"(d[12]), "+f"(d[13]), "+f"(d[14]), "+f"(d[15]),
          "+f"(d[16]), "+f"(d[17]), "+f"(d[18]), "+f"(d[19]), "+f"(d[20]), "+f"(d[21]), "+f"(d[22]), "+f"(d[23]),
          "+f"(d[24]), "+f"(d[25]), "+f"(d[26]), "+f"(d[27]), "+f"(d[28]), "+f"(d[29]), "+f"(d[30]), "+f"(d[31]),
          "+f"(d[32]), "+f"(d[33]), "+f"(d[34]), "+f"(d[35]), "+f"(d[36]), "+f"(d[37]), "+f"(d[38]), "+f"(d[39])
        : "l"(da), "l"(db), "n"(SCALE_D));
}
__device__ __forceinline__ void node_gemm(float (&d)[40], uint32_t wa, uint32_t xa) {
    const uint64_t da = desc_sw128(wa), db = desc_sw128(xa);
    wgmma_n80<0>(d, da, db);
    wgmma_n80<1>(d, da + 128, db + 2);
    wgmma_n80<1>(d, da + 256, db + 4);
    wgmma_n80<1>(d, da + 384, db + 6);
}
template <int NREG>
__device__ __forceinline__ void reg_fence(float (&d)[NREG]) {
    #pragma unroll
    for (int i = 0; i < NREG; i++) asm volatile("" : "+f"(d[i]) :: "memory");
}

__device__ __forceinline__ uint32_t pack_bf16(float lo, float hi) {
    uint32_t d; asm("cvt.rn.bf16x2.f32 %0, %1, %2;" : "=r"(d) : "f"(hi), "f"(lo)); return d;
}
__device__ __forceinline__ uint32_t fma_bf2(uint32_t a, uint32_t b, uint32_t c) {
    uint32_t d; asm("fma.rn.bf16x2 %0, %1, %2, %3;" : "=r"(d) : "r"(a), "r"(b), "r"(c)); return d;
}
__device__ __forceinline__ uint32_t add_bf2(uint32_t a, uint32_t b) {
    uint32_t d; asm("add.rn.bf16x2 %0, %1, %2;" : "=r"(d) : "r"(a), "r"(b)); return d;
}
__device__ __forceinline__ float ex2f(float x) {
    float y; asm("ex2.approx.ftz.f32 %0, %1;" : "=f"(y) : "f"(x)); return y;
}
__device__ __forceinline__ uint32_t fma_relu_bf2(uint32_t a, uint32_t b, uint32_t c) {
    uint32_t d; asm("fma.rn.relu.bf16x2 %0, %1, %2, %3;" : "=r"(d) : "r"(a), "r"(b), "r"(c)); return d;
}
__device__ __forceinline__ uint32_t gate_pair(float y0, float y1, uint32_t neb, uint32_t niea) {
    const uint32_t na = fma_bf2(pack_bf16(ex2f(y0), ex2f(y1)), neb, niea);
    const uint32_t r0 = ~na;
    const uint32_t e  = fma_relu_bf2(na, r0, 0x40EF40EFu);
    return fma_bf2(r0, e, r0);
}

__device__ __forceinline__ uint4 ld_relaxed_128(const uint4* p) {
    uint4 v;
    asm volatile("{\n\t.reg .b128 t;\n\tld.relaxed.gpu.global.b128 t, [%4];\n\tmov.b128 {%0,%1,%2,%3}, t;\n\t}"
                 : "=r"(v.x), "=r"(v.y), "=r"(v.z), "=r"(v.w) : "l"(p) : "memory");
    return v;
}
__device__ __forceinline__ void st_relaxed_128(uint4* p, uint4 v) {
    asm volatile("{\n\t.reg .b128 t;\n\tmov.b128 t, {%1,%2,%3,%4};\n\tst.relaxed.gpu.global.b128 [%0], t;\n\t}"
                 :: "l"(p), "r"(v.x), "r"(v.y), "r"(v.z), "r"(v.w) : "memory");
}
__device__ __forceinline__ void sts32(uint32_t addr, uint32_t a) { asm volatile("st.shared.u32 [%0], %1;" :: "r"(addr), "r"(a) : "memory"); }
__device__ __forceinline__ uint32_t atoms_inc_if(uint32_t addr, bool p, uint32_t dflt) {
    uint32_t r = dflt;
    asm volatile("{\n\t.reg .pred p;\n\tsetp.ne.u32 p, %2, 0;\n\t@p atom.shared.add.u32 %0, [%1], 1;\n\t}"
                 : "+r"(r) : "r"(addr), "r"((uint32_t)p) : "memory");
    return r;
}
__device__ __forceinline__ void sts64_if(uint32_t addr, uint32_t a, uint32_t b, bool p) {
    asm volatile("{\n\t.reg .pred p;\n\tsetp.ne.u32 p, %3, 0;\n\t@p st.shared.v2.u32 [%0], {%1,%2};\n\t}"
                 :: "r"(addr), "r"(a), "r"(b), "r"((uint32_t)p) : "memory");
}

__global__ void __launch_bounds__(NTHREADS, 1)
gatedgcn_kernel(const __nv_bfloat16* __restrict__ x, const __nv_bfloat16* __restrict__ e_attr,
                const int* __restrict__ src, const int* __restrict__ dst,
                const __nv_bfloat16* __restrict__ w_a, const __nv_bfloat16* __restrict__ w_b,
                const __nv_bfloat16* __restrict__ w_c, const __nv_bfloat16* __restrict__ w_u,
                const __nv_bfloat16* __restrict__ w_v, __nv_bfloat16* __restrict__ out) {
    extern __shared__ __align__(1024) unsigned char smem[];
    const uint32_t sb = (uint32_t)__cvta_generic_to_shared(smem);
    const int tid = threadIdx.x, lane = tid & 31;
    const int warp = uni(tid >> 5);
    const int cta = blockIdx.x;
    const int node0 = cta * NPB;
    const int g = lane >> 2, q = lane & 3;

    int* s_cnt  = (int*)(smem + SM_CNT);
    int* s_ncnt = (int*)(smem + SM_NCNT);
    volatile int* s_misc = (volatile int*)(smem + SM_MISC);

    auto load_weights = [&](int t, int nt) {
        #pragma unroll 1
        for (int i = t; i < 512; i += nt) {
            const uint32_t so = sb + SM_W + (i >> 3) * 128 + (((i ^ (i >> 3)) & 7) << 4);
            cp_async16(so + WS_B, w_b + i * 8);
            cp_async16(so + WS_V, w_v + i * 8);
            cp_async16(so + WS_A, w_a + i * 8);
            cp_async16(so + WS_U, w_u + i * 8);
        }
        if (t < 128) cp_async16(sb + SM_W + WS_C + (t >> 3) * 128 + (((t ^ (t >> 3)) & 7) << 4), w_c + t * 8);
    };

    auto store_rows = [&](const float (&d)[40], uint32_t base, int ld) {
        base += ((lane & 7) + ((lane >> 4) << 3)) * ld + ((warp & 3) * 16 + ((lane >> 3) & 1) * 8) * 2;
        #pragma unroll
        for (int w = 0; w < 10; w += 2)
            stsm_x4_t(base + w * 8 * ld,
                      pack_bf16(d[4 * w + 0], d[4 * w + 1]), pack_bf16(d[4 * w + 2], d[4 * w + 3]),
                      pack_bf16(d[4 * w + 4], d[4 * w + 5]), pack_bf16(d[4 * w + 6], d[4 * w + 7]));
    };
    auto neg_exp = [&](float (&d)[40], float scale, int slot) {
        float mx = 0.f;
        #pragma unroll
        for (int i = 0; i < 40; i++) { mx = fmaxf(mx, fabsf(d[i])); d[i] = -ex2f(d[i] * scale); }
        const uint32_t mb = __reduce_max_sync(0xffffffffu, __float_as_uint(mx));
        if (lane == 0) atomicMax((unsigned int*)&s_misc[slot], mb);
    };

    PROF(0);
    if (warp < NET / 32) {
        const int ebase = cta * CHUNK;
        const int nvec = (min(CHUNK, N_EDGES - ebase)) >> 2;
        int4 dv[4], sv[4];
        #pragma unroll
        for (int k = 0; k < 4; k++) {
            const int v = tid + k * NET;
            if (v < nvec) {
                dv[k] = __ldg((const int4*)(dst + ebase) + v);
                sv[k] = __ldg((const int4*)(src + ebase) + v);
            }
        }
        if (tid < 136 + 80 + 5 && tid != 136 + 80) s_cnt[tid] = 0;
        bar_sync(1, NET);
        PROF(1);

        #pragma unroll
        for (int k = 0; k < 4; k++) {
            const int v = tid + k * NET;
            if (v < nvec) {
                const int dd[4] = {dv[k].x, dv[k].y, dv[k].z, dv[k].w};
                const int ss[4] = {sv[k].x, sv[k].y, sv[k].z, sv[k].w};
                uint32_t b[4], rank[4];
                #pragma unroll
                for (int j = 0; j < 4; j++) { b[j] = (uint32_t)dd[j] / NPB; rank[j] = (uint32_t)atomicAdd(&s_cnt[b[j]], 1); }
                #pragma unroll
                for (int j = 0; j < 4; j++) {
                    const uint32_t rec = (((uint32_t)(v * 4 + j) - b[j]) * NPB + (uint32_t)dd[j]) * N_NODES + (uint32_t)ss[j];
                    sts32(sb + SM_STAGE + (b[j] * SEG_LD + min(rank[j], (uint32_t)SEGCAP)) * 4, rec);
                }
            }
        }
        const int sg = tid / UMAIN, su = tid - sg * UMAIN;
        const bool act = sg < SPP, act_last = sg + (UPT - 1) * SPP < NB;
        bar_sync(8, NET + 32);
        PROF(2);
        const uint32_t tag = (((uint32_t)s_misc[0] + 1u) & 0xFFFFFFu) << 8;
        if (act) {
            uint4 pu[UPT];
            uint32_t tmask = 0;
            const uint32_t a = sb + SM_STAGE + (sg * SEG_LD + 3 * su) * 4;
            #pragma unroll
            for (int k = 0; k < UPT; k++) {
                const int cnt = s_cnt[sg + k * SPP];
                pu[k].x = lds32(a + k * SPP * SEG_LD * 4); pu[k].y = lds32(a + k * SPP * SEG_LD * 4 + 4); pu[k].z = lds32(a + k * SPP * SEG_LD * 4 + 8);
                const int extra = min(max(cnt - 3 * UMAIN, 0), 31);
                pu[k].w = tag | (uint32_t)extra << 2 | (uint32_t)min(max(cnt - 3 * su, 0), 3);
                if (extra > 0) tmask |= 1u << k;
            }
            uint4* gq = g_seg + ((size_t)sg * NB + cta) * UMAIN + su;
            #pragma unroll
            for (int k = 0; k < UPT; k++)
                if (k < UPT - 1 || act_last) st_relaxed_128(gq + (size_t)k * SPP * NB * UMAIN, pu[k]);
            if (su >= UTAIL) tmask = 0;
            while (tmask) {
                const int b = sg + (__ffs(tmask) - 1) * SPP;
                tmask &= tmask - 1;
                const uint32_t ta = sb + SM_STAGE + (b * SEG_LD + 3 * (UMAIN + su)) * 4;
                st_relaxed_128(g_tail + ((size_t)b * NB + cta) * UTAIL + su, make_uint4(lds32(ta), lds32(ta + 4), lds32(ta + 8), tag));
            }
        }
        PROF(3);
        bar_sync(3, NTHREADS);
        if (warp < 8) {
            float d[40];
            wgmma_fence();
            node_gemm(d, sb + SM_W + (warp < 4 ? WS_A : WS_U), sb + SM_XOWN);
            wgmma_commit();
            wgmma_wait<0>();
            reg_fence(d);
            if (warp < 4) neg_exp(d, L2E, 4);
            store_rows(d, sb + (warp < 4 ? SM_IEA : SM_U), U_LD);
        } else {
            #pragma unroll
            for (int k = 0; k < 4; k++) {
                const int i = tid - 256 + k * 128;
                const int l = i >> 4, j = (i >> 1) & 7, h = i & 1;
                const int f = 32 * (j >> 2) + 8 * (l >> 3) + 2 * (j & 3) + ((l >> 2) & 1);
                const int r = 4 * (l & 3) + 2 * h;
                const unsigned char* wc = smem + SM_W + WS_C + (f & 7) * 2;
                const float c0 = __bfloat162float(*(const __nv_bfloat16*)(wc + r * 128 + (((f >> 3) ^ (r & 7)) << 4)));
                const float c1 = __bfloat162float(*(const __nv_bfloat16*)(wc + (r + 1) * 128 + (((f >> 3) ^ ((r + 1) & 7)) << 4)));
                ((uint32_t*)(smem + SM_WCF))[((i >> 2) & 3) * 128 + l * 4 + (i & 3)] = pack_bf16(c0 * -L2E, c1 * -L2E);
            }
        }
        #pragma unroll 4
        for (int i = tid; i < NULLT / 16; i += NET) sts128(sb + SM_LIST + i * 16, NULL_W0, 0u, NULL_W0, 0u);
        PROF(15);
        const uint4* gp = g_seg + (size_t)cta * NB * UMAIN + tid;
        uint4 rec[UPT];
        #pragma unroll
        for (int k = 0; k < UPT; k++) {
            rec[k].w = tag;
            if (k < UPT - 1 ? act : act_last) rec[k] = ld_relaxed_128(gp + k * SPP * UMAIN);
        }
        bar_sync(1, NET);
        PROF(4);
        {
            uint32_t tmask = 0, pend = (1u << UPT) - 1;
            for (int tries = 0; pend; tries++) {
                #pragma unroll
                for (int k = 0; k < UPT; k++) {
                    if (pend >> k & 1) {
                        const bool ok = ((rec[k].w ^ tag) >> 8) == 0;
                        if (__all_sync(0xffffffffu, ok)) {
                            pend &= ~(1u << k);
                            const uint32_t w[3] = {rec[k].x, rec[k].y, rec[k].z};
                            const int n = rec[k].w & 3;
                            uint32_t t[3], el[3], dl[3], r[3];
                            #pragma unroll
                            for (int j = 0; j < 3; j++) {
                                t[j] = w[j] / N_NODES;
                                el[j] = t[j] / NPB;
                                dl[j] = t[j] - el[j] * NPB;
                                r[j] = atoms_inc_if(sb + SM_NCNT + dl[j] * 4, j < n, 0u);
                            }
                            #pragma unroll
                            for (int j = 0; j < 3; j++)
                                sts64_if(sb + SM_LIST + dl[j] * LIST_LD + min(r[j], (uint32_t)CAPN) * 8,
                                         (w[j] - t[j] * N_NODES) << 8, ((sg + k * SPP) * CHUNK + el[j]) * 32u, j < n);
                            if (rec[k].w & 0x7C) tmask |= 1u << k;
                        } else if (!ok) rec[k] = ld_relaxed_128(gp + k * SPP * UMAIN);
                    }
                }
                if (tries > 400000) { s_misc[1] = 1; break; }
            }
            if (su >= UTAIL) tmask = 0;
            while (tmask) {
                const int k = __ffs(tmask) - 1;
                tmask &= tmask - 1;
                const int pr = sg + k * SPP;
                const int extra = (ld_relaxed_128(gp + k * SPP * UMAIN).w >> 2) & 31;
                uint4 v;
                int tries = 0;
                do { v = ld_relaxed_128(g_tail + ((size_t)cta * NB + pr) * UTAIL + su); } while (v.w != tag && ++tries < 400000);
                if (v.w != tag || extra > 3 * UTAIL) s_misc[1] = 1;
                else {
                    const uint32_t w[3] = {v.x, v.y, v.z};
                    #pragma unroll 1
                    for (int j = 0; j < 3; j++) {
                        if (3 * su + j < extra) {
                            const uint32_t ww = j == 0 ? w[0] : j == 1 ? w[1] : w[2];
                            const uint32_t t = ww / N_NODES, e = t / NPB, dl = t - e * NPB;
                            const uint32_t rr = (uint32_t)atomicAdd(&s_ncnt[dl], 1);
                            sts64(sb + SM_LIST + dl * LIST_LD + min(rr, (uint32_t)CAPN) * 8, (ww - t * N_NODES) << 8, (pr * CHUNK + e) * 32u);
                        }
                    }
                }
            }
        }
        PROF(5);
    } else {
        const int wtid = tid - NET;
        {
            const uint32_t so = (wtid >> 3) * 128 + (((wtid ^ (wtid >> 3)) & 7) << 4);
            #pragma unroll
            for (int k = 0; k < 5; k++) {
                const int r = (wtid >> 3) + 16 * k;
                const bool ok = r < NPB && node0 + r < N_NODES;
                cp_async16_zfill(sb + SM_XOWN + so + k * 2048, x + (ok ? (size_t)node0 * 64 + wtid * 8 + k * 1024 : 0), ok ? 16 : 0);
            }
            #pragma unroll
            for (int k = 0; k < 4; k++) {
                cp_async16(sb + SM_W + WS_V + so + k * 2048, w_v + wtid * 8 + k * 1024);
                cp_async16(sb + SM_W + WS_B + so + k * 2048, w_b + wtid * 8 + k * 1024);
            }
            cp_commit();
            #pragma unroll
            for (int k = 0; k < 4; k++) {
                cp_async16(sb + SM_W + WS_A + so + k * 2048, w_a + wtid * 8 + k * 1024);
                cp_async16(sb + SM_W + WS_U + so + k * 2048, w_u + wtid * 8 + k * 1024);
            }
            cp_async16(sb + SM_W + WS_C + so, w_c + wtid * 8);
            cp_commit();
        }
        if (wtid >= 96) {
            if (lane == 0) {
                uint32_t ticket;
                asm volatile("atom.relaxed.gpu.global.inc.u32 %0, [%1], %2;" : "=r"(ticket) : "l"(&g_ticket), "r"((uint32_t)NB * (1u << 24) - 1u) : "memory");
                s_misc[0] = (int)(ticket / NB);
            }
            __syncwarp();
            bar_arrive(8, NET + 32);
        }
        if (wtid < 8) sts128(sb + SM_LIST + NULLT + wtid * 16, NULL_W0, 0u, NULL_W0, 0u);
        if (wtid >= 8 && wtid < 11) s_misc[wtid - 3] = 0;
        if (wtid >= 32 && wtid < 64) s_misc[wtid - 24] = 0;
        cp_wait<1>();
        fence_async();
        bar_sync(2, 128);
        PROFG(10);
        {
            float db[40], dv[40];
            wgmma_fence();
            node_gemm(dv, sb + SM_W + WS_V, sb + SM_XOWN);
            wgmma_commit();
            node_gemm(db, sb + SM_W + WS_B, sb + SM_XOWN);
            wgmma_commit();
            wgmma_wait<1>();
            reg_fence(dv);
            store_rows(dv, sb + SM_T + 128, T_LD);
            wgmma_wait<0>();
            reg_fence(db);
            neg_exp(db, -L2E, 5);
            store_rows(db, sb + SM_T, T_LD);
        }
        bar_sync(2, 128);
        PROFG(11);
        {
            uint4 v[10];
            #pragma unroll
            for (int k = 0; k < 10; k++)
                v[k] = lds128(sb + SM_T + ((wtid >> 4) + 8 * k) * T_LD + (wtid & 1) * 128 + ((wtid >> 1) & 7) * 16);
            #pragma unroll
            for (int k = 0; k < 10; k++) {
                const int r = (wtid >> 4) + 8 * k;
                if (node0 + r == N_NODES) v[k].x = v[k].y = v[k].z = v[k].w = (wtid & 1) ? 0u : 0xFF80FF80u;
                if (r < NPB && node0 + r <= N_NODES) g_tab[(size_t)node0 * 16 + wtid + k * 128] = v[k];
            }
        }
        cp_wait<0>();
        fence_async();
        bar_arrive(3, NTHREADS);
        bar_sync(2, 128);
        PROFG(12);
        if (wtid >= 96) {
            const uint32_t ftag = (uint32_t)s_misc[0] + 1u;
            if (lane == 0)
                asm volatile("st.release.gpu.global.u64 [%0], %1;"
                             :: "l"(&g_flag[cta]), "l"(((unsigned long long)ftag << 32) | (uint32_t)s_misc[5]) : "memory");
            __syncwarp();
            uint32_t mx;
            for (int tries = 0;; tries++) {
                __nanosleep(150);
                bool ok = true;
                mx = 0;
                #pragma unroll
                for (int k = 0; k < 3; k++) {
                    if (k < 2 || lane < NB / 2 - 64) {
                        const uint4 f = ld_relaxed_128((const uint4*)g_flag + lane + 32 * k);
                        ok = ok && f.y == ftag && f.w == ftag;
                        mx = max(mx, max(f.x, f.z));
                    }
                }
                if (__all_sync(0xffffffffu, ok)) break;
                if (tries > 100000) { mx = 0x7F800000u; break; }
            }
            asm volatile("fence.acq_rel.gpu;" ::: "memory");
            mx = __reduce_max_sync(0xffffffffu, mx);
            if (lane == 0) s_misc[6] = (int)mx;
        }
        PROFG(9);
    }
    __syncthreads();
    PROF(6);
    const bool bad_list = s_misc[1] != 0 ||
        __any_sync(0xffffffffu, max(max(s_ncnt[lane], s_ncnt[lane + 32]), s_ncnt[min(lane + 64, NPB - 1)]) > CAPN);

    auto reduce_rows = [&](float (&sum)[4], const uint32_t (&den)[8], const uint32_t (&num)[8]) {
        float s1[4] = {0.f, 0.f, 0.f, 0.f}, s2[4] = {0.f, 0.f, 0.f, 0.f};
        uint32_t ln;
        asm volatile("mov.u32 %0, %%laneid;" : "=r"(ln));
        #pragma unroll
        for (int j = 0; j < 4; j++) {
            const uint32_t sel = ((ln >> 2) & 3) == j ? 0x3F803F80u : 0u;
            mma_k16(s1, sel, 0u, 0u, sel, movm(den[j]), movm(num[j]), s1[0], s1[1], s1[2], s1[3]);
            mma_k16(s2, sel, 0u, 0u, sel, movm(den[j + 4]), movm(num[j + 4]), s2[0], s2[1], s2[2], s2[3]);
        }
        #pragma unroll
        for (int i = 0; i < 4; i++) sum[i] = ln < 16 ? s1[i] : s2[i];
    };
    auto write_node = [&](int node, const float (&sum)[4], int f0) {
        if (node0 + node < N_NODES) {
            const uint32_t iw = lds32(sb + SM_IEA + node * U_LD + f0 * 2);
            const uint32_t uw = lds32(sb + SM_U + node * U_LD + f0 * 2);
            const uint32_t xw = lds32(sb + SM_XOWN + node * 128 + (((f0 >> 3) ^ (node & 7)) << 4) + (f0 & 7) * 2);
            const float i0 = __uint_as_float(iw << 16), i1 = __uint_as_float(iw & 0xFFFF0000u);
            const float z0 = __uint_as_float(uw << 16) + __fdividef(sum[2] * i0, sum[0] * i0 - RSCALE * 1e-6f);
            const float z1 = __uint_as_float(uw & 0xFFFF0000u) + __fdividef(sum[3] * i1, sum[1] * i1 - RSCALE * 1e-6f);
            const float o0 = __uint_as_float(xw << 16) + fmaxf(z0, 0.f);
            const float o1 = __uint_as_float(xw & 0xFFFF0000u) + fmaxf(z1, 0.f);
            *(uint32_t*)(out + (size_t)(node0 + node) * 64 + f0) = pack_bf16(o0, o1);
        }
    };
    const char* eq = (const char*)e_attr + q * 8;
    const uint32_t la = sb + SM_LIST + g * 8;
    const bool fast = !bad_list && __int_as_float(s_misc[4]) + __int_as_float(s_misc[6]) <= RANGE_MAX;

    if (fast) {
        auto job_range = [&](int j, int& tb, int& te) {
            tb = NULLT; te = NULLT + 128;
            if (j >= NJOBS) return -1;
            const int n = j < NWHOLE ? j : NWHOLE + ((j - NWHOLE) >> 1);
            const int nt = max(1, (s_ncnt[n] + 15) >> 4);
            const int mid = j < NWHOLE ? nt : (nt + 1) >> 1;
            const bool second = j >= NWHOLE && ((j - NWHOLE) & 1);
            if (!second) { tb = n * LIST_LD; te = tb + mid * 128; }
            else if (mid < nt) { tb = n * LIST_LD + mid * 128; te = n * LIST_LD + nt * 128; }
            return n;
        };
        const char* tabq = (const char*)g_tab + q * 32;
        asm volatile("" : "+l"(tabq));
        uint32_t wcf[16];
        #pragma unroll
        for (int i = 0; i < 4; i++) {
            const uint4 v = lds128(sb + SM_WCF + i * 512 + lane * 16);
            wcf[4 * i] = v.x; wcf[4 * i + 1] = v.y; wcf[4 * i + 2] = v.z; wcf[4 * i + 3] = v.w;
        }
        uint32_t eb[2][8], hq[2][8], ev[4];
        const char *p0, *p1;
        bool v0, v1;
        auto load_rec = [&](int tt) {
            const uint2 r0 = lds64(la + tt), r1 = lds64(la + tt + 64);
            p0 = tabq + r0.x; p1 = tabq + r1.x;
            v0 = r0.x != NULL_W0; v1 = r1.x != NULL_W0;
            ldg64_stream(ev[0], ev[2], eq + r0.y);
            ldg64_stream(ev[1], ev[3], eq + r1.y);
        };
        auto load_half = [&](int h) {
            ldg128(&eb[0][4 * h], p0 + 128 * h); ldg128(&eb[1][4 * h], p1 + 128 * h);
            ldg128(&hq[0][4 * h], p0 + 16 + 128 * h); ldg128(&hq[1][4 * h], p1 + 16 + 128 * h);
        };
        auto load_rows = [&]() { load_half(0); load_half(1); };
        const int yes = s_misc[1] == 0;
        int t, te;
        int node = job_range(warp, t, te);
        load_rec(t);
        load_rows();
        while (true) {
            int nnode = 0;
            uint32_t iea[8], den[8], num[8];
            {
                const uint4 w0 = lds128(sb + SM_IEA + node * U_LD + q * 16), w1 = lds128(sb + SM_IEA + node * U_LD + 64 + q * 16);
                iea[0] = w0.x; iea[1] = w0.y; iea[2] = w0.z; iea[3] = w0.w; iea[4] = w1.x; iea[5] = w1.y; iea[6] = w1.z; iea[7] = w1.w;
            }
            #pragma unroll
            for (int j = 0; j < 8; j++) { den[j] = 0u; num[j] = 0u; }
            bool last;
            do {
                const uint32_t a0 = v0 ? ev[0] : 0u, a1 = v1 ? ev[1] : 0u, a2 = v0 ? ev[2] : 0u, a3 = v1 ? ev[3] : 0u;
                t += 128;
                last = t == te;
                if (last) nnode = job_range(uni((int)atoms_inc_if(sb + SM_MISC + 12, lane == 0, 0u)) + NWARPS, t, te);
                load_rec(t);
                #pragma unroll
                for (int h = 0; h < 2; h++) {
                    if (h == 1) { int y = yes; asm volatile("" : "+r"(y) :: "memory"); if (!y) break; }
                    float d[16];
                    #pragma unroll
                    for (int j = 0; j < 4; j++)
                        mma_k16(&d[4 * j], a0, a1, a2, a3, wcf[8 * h + 2 * j], wcf[8 * h + 2 * j + 1], 0.f, 0.f, 0.f, 0.f);
                    #pragma unroll
                    for (int jj = 0; jj < 4; jj++) {
                        const int j = 4 * h + jj;
                        const uint32_t ra = gate_pair(d[4 * jj], d[4 * jj + 1], eb[0][j], iea[j]);
                        const uint32_t rb = gate_pair(d[4 * jj + 2], d[4 * jj + 3], eb[1][j], iea[j]);
                        den[j] = add_bf2(add_bf2(den[j], ra), rb);
                        num[j] = fma_bf2(rb, hq[1][j], fma_bf2(ra, hq[0][j], num[j]));
                    }
                    load_half(h);
                }
            } while (!last);
            const int f0 = 32 * (g >> 2) + 8 * q + 2 * (g & 3);
            float sum[4];
            reduce_rows(sum, den, num);
            bool mine = true;
            if (node >= NWHOLE) {
                const uint32_t st = sb + SM_STATE + (node - NWHOLE) * 4, pa = sb + SM_PART + (node - NWHOLE) * 512 + lane * 16;
                mine = uni((int)atoms_inc_if(st, lane == 0, 0u)) != 0;
                if (!mine) {
                    sts128(pa, __float_as_uint(sum[0]), __float_as_uint(sum[1]), __float_as_uint(sum[2]), __float_as_uint(sum[3]));
                    __threadfence_block();
                    __syncwarp();
                    if (lane == 0) atomicAdd((int*)(smem + (st - sb)), 2);
                } else {
                    while (*(volatile int*)(smem + (st - sb)) < 4) {}
                    __threadfence_block();
                    const uint4 o = lds128(pa);
                    sum[0] += __uint_as_float(o.x); sum[1] += __uint_as_float(o.y);
                    sum[2] += __uint_as_float(o.z); sum[3] += __uint_as_float(o.w);
                }
            }
            if (mine) write_node(node, sum, f0);
            if (nnode < 0) break;
            node = nnode;
        }
        PROFE();
    } else {
        float2* acc = g_acc + (size_t)cta * NPB * 64;
        __syncthreads();
        load_weights(tid, NTHREADS);
        cp_commit();
        for (int i = tid; i < NPB * 64; i += NTHREADS) acc[i] = make_float2(0.f, 0.f);
        cp_wait<0>();
        int scan_pos = bad_list ? 0 : N_EDGES;
        int pend = 0, pv = 0;
        int4 d4 = make_int4(0, 0, 0, 0);
        bool more = true;
        while (more) {
            if (bad_list) {
                __syncthreads();
                if (tid < 80) s_ncnt[tid] = 0;
                __syncthreads();
                while (true) {
                    const int dd[4] = {d4.x, d4.y, d4.z, d4.w};
                    #pragma unroll
                    for (int j = 0; j < 4; j++) {
                        if (pend >> j & 1) {
                            const int dl = dd[j] - node0;
                            const int r = atomicAdd(&s_ncnt[dl], 1);
                            if (r < CAPN) {
                                const int e = pv * 4 + j;
                                sts64(sb + SM_LIST + dl * LIST_LD + r * 8, (uint32_t)__ldg(src + e) << 8, (uint32_t)e * 32u);
                                pend &= ~(1 << j);
                            }
                        }
                    }
                    if (__syncthreads_or(pend)) break;
                    if (scan_pos >= N_EDGES) { more = false; break; }
                    pv = (scan_pos >> 2) + tid;
                    if (pv < N_EDGES / 4) {
                        d4 = __ldg((const int4*)dst + pv);
                        pend = ((uint32_t)(d4.x - node0) < NPB ? 1 : 0) | ((uint32_t)(d4.y - node0) < NPB ? 2 : 0)
                             | ((uint32_t)(d4.z - node0) < NPB ? 4 : 0) | ((uint32_t)(d4.w - node0) < NPB ? 8 : 0);
                    }
                    scan_pos += NTHREADS * 4;
                }
            } else {
                more = false;
                __syncthreads();
            }
            const uint32_t wrow = sb + SM_W + (lane & 15) * 128;
            #pragma unroll 1
            for (int job = warp; job < NPB * 4; job += NWARPS) {
                const int n = job >> 2, jp = job & 3;
                const int cnt = min(s_ncnt[n], CAPN);
                if (cnt == 0) continue;
                const uint32_t wa = wrow + (((2 * jp + (lane >> 4)) ^ (lane & 7)) << 4);
                float ca[8] = {0.f, 0.f, 0.f, 0.f, 0.f, 0.f, 0.f, 0.f};
                #pragma unroll
                for (int k = 0; k < 4; k++) {
                    const uint32_t a0 = lds32(sb + SM_XOWN + n * 128 + (((2 * k) ^ (n & 7)) << 4) + q * 4);
                    const uint32_t a2 = lds32(sb + SM_XOWN + n * 128 + (((2 * k + 1) ^ (n & 7)) << 4) + q * 4);
                    uint32_t b[4];
                    ldsm_x4_t(b, wa + WS_A + k * 2048);
                    mma_k16(&ca[0], a0, a0, a2, a2, b[0], b[1], ca[0], ca[1], ca[2], ca[3]);
                    mma_k16(&ca[4], a0, a0, a2, a2, b[2], b[3], ca[4], ca[5], ca[6], ca[7]);
                }
                float sd[4] = {0.f, 0.f, 0.f, 0.f}, sn[4] = {0.f, 0.f, 0.f, 0.f};
                #pragma unroll 1
                for (int i0 = 0; i0 < cnt; i0 += 16) {
                    const bool v0 = i0 + g < cnt, v1 = i0 + g + 8 < cnt;
                    const uint2 r0 = lds64(sb + SM_LIST + n * LIST_LD + (v0 ? i0 + g : 0) * 8);
                    const uint2 r1 = lds64(sb + SM_LIST + n * LIST_LD + (v1 ? i0 + g + 8 : 0) * 8);
                    const uint32_t* x0 = (const uint32_t*)((const char*)x + (r0.x >> 1)) + q;
                    const uint32_t* x1 = (const uint32_t*)((const char*)x + (r1.x >> 1)) + q;
                    const uint32_t* e0 = (const uint32_t*)((const char*)e_attr + r0.y) + q;
                    const uint32_t* e1 = (const uint32_t*)((const char*)e_attr + r1.y) + q;
                    float gg[8], hh[8] = {0.f, 0.f, 0.f, 0.f, 0.f, 0.f, 0.f, 0.f};
                    uint32_t b[4];
                    {
                        const uint32_t a0 = __ldg(e0), a1 = __ldg(e1), a2 = __ldg(e0 + 4), a3 = __ldg(e1 + 4);
                        ldsm_x4_t(b, wa + WS_C);
                        mma_k16(&gg[0], a0, a1, a2, a3, b[0], b[1], ca[0], ca[1], ca[2], ca[3]);
                        mma_k16(&gg[4], a0, a1, a2, a3, b[2], b[3], ca[4], ca[5], ca[6], ca[7]);
                    }
                    #pragma unroll
                    for (int k = 0; k < 4; k++) {
                        const uint32_t a0 = __ldg(x0 + 8 * k), a1 = __ldg(x1 + 8 * k), a2 = __ldg(x0 + 8 * k + 4), a3 = __ldg(x1 + 8 * k + 4);
                        ldsm_x4_t(b, wa + WS_B + k * 2048);
                        mma_k16(&gg[0], a0, a1, a2, a3, b[0], b[1], gg[0], gg[1], gg[2], gg[3]);
                        mma_k16(&gg[4], a0, a1, a2, a3, b[2], b[3], gg[4], gg[5], gg[6], gg[7]);
                        ldsm_x4_t(b, wa + WS_V + k * 2048);
                        mma_k16(&hh[0], a0, a1, a2, a3, b[0], b[1], hh[0], hh[1], hh[2], hh[3]);
                        mma_k16(&hh[4], a0, a1, a2, a3, b[2], b[3], hh[4], hh[5], hh[6], hh[7]);
                    }
                    #pragma unroll
                    for (int i = 0; i < 8; i++) {
                        const float eta = ((i & 2) ? v1 : v0) ? 1.0f / (1.0f + ex2f(gg[i] * -L2E)) : 0.f;
                        const int o = (i >> 2) * 2 + (i & 1);
                        sd[o] += eta;
                        sn[o] = fmaf(eta, hh[i], sn[o]);
                    }
                }
                #pragma unroll
                for (int i = 0; i < 4; i++) {
                    #pragma unroll
                    for (int o = 4; o < 32; o <<= 1) {
                        sd[i] += __shfl_xor_sync(0xffffffffu, sd[i], o);
                        sn[i] += __shfl_xor_sync(0xffffffffu, sn[i], o);
                    }
                }
                if (g == 0) {
                    #pragma unroll
                    for (int i = 0; i < 4; i++) {
                        float2* pa = acc + n * 64 + jp * 16 + (i >> 1) * 8 + 2 * q + (i & 1);
                        *pa = make_float2(pa->x + sd[i], pa->y + sn[i]);
                    }
                }
            }
        }
        __syncthreads();
        for (int i = tid; i < NPB * 64; i += NTHREADS) {
            const int n = i >> 6, f = i & 63;
            if (node0 + n < N_NODES) {
                const float2 a = acc[i];
                const float u = __bfloat162float(*(const __nv_bfloat16*)(smem + SM_U + n * U_LD + f * 2));
                const float xv = __bfloat162float(*(const __nv_bfloat16*)(smem + SM_XOWN + n * 128 + (((f >> 3) ^ (n & 7)) << 4) + (f & 7) * 2));
                out[(size_t)(node0 + n) * 64 + f] = __float2bfloat16(xv + fmaxf(u + a.y / (a.x + 1e-6f), 0.f));
            }
        }
    }
}

}

extern "C" void kernel_launch(void* const* d_in, const int* in_sizes, int n_in, void* d_out, int out_size) {
    (void)in_sizes; (void)n_in; (void)out_size;
    constexpr int SMEM = SM_TOTAL + 128;
    cudaFuncSetAttribute(gatedgcn_kernel, cudaFuncAttributeMaxDynamicSharedMemorySize, SMEM);
    gatedgcn_kernel<<<NB, NTHREADS, SMEM>>>(
        (const __nv_bfloat16*)d_in[0], (const __nv_bfloat16*)d_in[1], (const int*)d_in[2], (const int*)d_in[3],
        (const __nv_bfloat16*)d_in[4], (const __nv_bfloat16*)d_in[5], (const __nv_bfloat16*)d_in[6],
        (const __nv_bfloat16*)d_in[7], (const __nv_bfloat16*)d_in[8], (__nv_bfloat16*)d_out);
}
```

```cpp
#include <cuda_runtime.h>
#include <cuda_bf16.h>
#include <stdint.h>

namespace {

constexpr int N_NODES  = 10000;
constexpr int N_EDGES  = 640000;
constexpr int NB       = 132;
constexpr int NPB      = 76;
constexpr int CHUNK    = 4864;
constexpr int UMAIN    = 10;
constexpr int SEGCAP   = 6 * UMAIN;
constexpr int WVEC     = CHUNK / 8;
constexpr int SEG_LD   = SEGCAP + 1;
constexpr int CAPN     = 112;
constexpr int LIST_LD  = (CAPN + 1) * 8;
constexpr int NTHREADS = 512;
constexpr int NWARPS   = NTHREADS / 32;
constexpr int NET      = 384;
constexpr int NSPLIT   = 12;
constexpr int NWHOLE   = NPB - NSPLIT;
constexpr int NJOBS    = NWHOLE + 2 * NSPLIT;
constexpr int SPP      = NET / UMAIN;
constexpr int UPT      = (NB + SPP - 1) / SPP;
constexpr int TAIL     = NB * NB * UMAIN;
static_assert(UMAIN % 2 == 0 && WVEC <= 2 * NET, "exchange geometry");
static_assert(NB * NPB > N_NODES && NB * CHUNK >= N_EDGES, "coverage");

constexpr int U_LD = 144;
constexpr int T_LD = 272;

constexpr int SM_XOWN  = 0;
constexpr int SM_LIST  = SM_XOWN + 80 * 128;
constexpr int SM_STAGE = SM_LIST;
constexpr int NULLT    = NPB * LIST_LD;
constexpr int SM_T     = SM_LIST + NULLT - 80 * T_LD;
constexpr int SM_W     = (SM_LIST + NULLT + 128 + 1023) / 1024 * 1024;
constexpr int W_BYTES  = (4 * 64 + 16) * 128;
constexpr int SM_IEA   = SM_W;
constexpr int SM_PART  = SM_W + 16384;
constexpr int SM_U     = SM_W + W_BYTES;
constexpr int SM_WCF   = SM_U + 80 * U_LD;
constexpr int SM_CNT   = SM_WCF + 2048;
constexpr int SM_NCNT  = SM_CNT + 2 * 136 * 4;
constexpr int SM_MISC  = SM_NCNT + 80 * 4;
constexpr int SM_STATE = SM_MISC + 8 * 4;
constexpr int SM_DCNT  = SM_STATE + 32 * 4;
constexpr int SM_DUMP  = SM_DCNT + 32 * 4;
constexpr int SM_TOTAL = SM_DUMP + 32 * 8;
static_assert(SM_STAGE + NB * SEG_LD * 4 <= SM_T && SM_T % 16 == 0, "staging fits");
static_assert(SM_W % 16 == 0 && NULLT % 16 == 0, "alignment");
static_assert((unsigned long long)CHUNK * NPB * N_NODES <= 0xFFFFFFFFull, "record fits 32 bits");
static_assert(80 * U_LD <= 16384 && NSPLIT <= 32, "aliases fit");
static_assert(SM_TOTAL <= 134144 - 256, "fits the 132 KB carve-out");

constexpr int WS_B = 0, WS_V = 8192, WS_A = 16384, WS_U = 24576, WS_C = 32768;

constexpr uint32_t NULL_W0 = (uint32_t)N_NODES * 256u;
constexpr float L2E = 1.4426950408889634f;
constexpr float RSCALE = 17.906f;
constexpr float RANGE_MAX = 61.0f;

__device__ __align__(128) unsigned int g_epoch[NB * 8];
__device__ __align__(128) unsigned long long g_flag[NB];
__device__ __align__(128) uint4 g_seg[(size_t)4 * NB * NB * UMAIN];
__device__ __align__(256) uint4 g_tab[(size_t)(N_NODES + 1) * 16];
__device__ float2 g_acc[(size_t)NB * NPB * 64];

#define PROFE() do {} while (0)
#define PROF(i) do {} while (0)
#define PROFG(i) do {} while (0)

__device__ __forceinline__ void cp_async16(uint32_t dst, const void* src) {
    asm volatile("cp.async.cg.shared.global [%0], [%1], 16;" :: "r"(dst), "l"(src) : "memory");
}
__device__ __forceinline__ void cp_async16_zfill(uint32_t dst, const void* src, int sz) {
    asm volatile("cp.async.cg.shared.global [%0], [%1], 16, %2;" :: "r"(dst), "l"(src), "r"(sz) : "memory");
}
__device__ __forceinline__ void cp_commit() { asm volatile("cp.async.commit_group;" ::: "memory"); }
template <int N> __device__ __forceinline__ void cp_wait() { asm volatile("cp.async.wait_group %0;" :: "n"(N) : "memory"); }
__device__ __forceinline__ void fence_async() { asm volatile("fence.proxy.async.shared::cta;" ::: "memory"); }
__device__ __forceinline__ void wgmma_fence() { asm volatile("wgmma.fence.sync.aligned;" ::: "memory"); }
__device__ __forceinline__ void wgmma_commit() { asm volatile("wgmma.commit_group.sync.aligned;" ::: "memory"); }
template <int N> __device__ __forceinline__ void wgmma_wait() { asm volatile("wgmma.wait_group.sync.aligned %0;" :: "n"(N) : "memory"); }
__device__ __forceinline__ void bar_sync(int id, int n) { asm volatile("bar.sync %0, %1;" :: "r"(id), "r"(n) : "memory"); }
__device__ __forceinline__ void bar_arrive(int id, int n) { asm volatile("bar.arrive %0, %1;" :: "r"(id), "r"(n) : "memory"); }
__device__ __forceinline__ int uni(int v) { return __shfl_sync(0xffffffffu, v, 0); }

__device__ __forceinline__ void ldsm_x4_t(uint32_t (&r)[4], uint32_t addr) {
    asm volatile("ldmatrix.sync.aligned.m8n8.x4.trans.shared.b16 {%0,%1,%2,%3}, [%4];"
                 : "=r"(r[0]), "=r"(r[1]), "=r"(r[2]), "=r"(r[3]) : "r"(addr) : "memory");
}
__device__ __forceinline__ void stsm_x4_t(uint32_t addr, uint32_t r0, uint32_t r1, uint32_t r2, uint32_t r3) {
    asm volatile("stmatrix.sync.aligned.m8n8.x4.trans.shared.b16 [%0], {%1,%2,%3,%4};"
                 :: "r"(addr), "r"(r0), "r"(r1), "r"(r2), "r"(r3) : "memory");
}
__device__ __forceinline__ uint32_t movm(uint32_t a) {
    uint32_t d; asm volatile("movmatrix.sync.aligned.m8n8.trans.b16 %0, %1;" : "=r"(d) : "r"(a)); return d;
}
__device__ __forceinline__ uint32_t lds32(uint32_t addr) {
    uint32_t v; asm volatile("ld.shared.u32 %0, [%1];" : "=r"(v) : "r"(addr) : "memory"); return v;
}
__device__ __forceinline__ uint2 lds64(uint32_t addr) {
    uint2 v; asm volatile("ld.shared.v2.u32 {%0,%1}, [%2];" : "=r"(v.x), "=r"(v.y) : "r"(addr) : "memory"); return v;
}
__device__ __forceinline__ uint4 lds128(uint32_t addr) {
    uint4 v; asm volatile("ld.shared.v4.u32 {%0,%1,%2,%3}, [%4];" : "=r"(v.x), "=r"(v.y), "=r"(v.z), "=r"(v.w) : "r"(addr) : "memory"); return v;
}
__device__ __forceinline__ void sts64(uint32_t addr, uint32_t a, uint32_t b) {
    asm volatile("st.shared.v2.u32 [%0], {%1,%2};" :: "r"(addr), "r"(a), "r"(b) : "memory");
}
__device__ __forceinline__ void sts128(uint32_t addr, uint32_t a, uint32_t b, uint32_t c, uint32_t d) {
    asm volatile("st.shared.v4.u32 [%0], {%1,%2,%3,%4};" :: "r"(addr), "r"(a), "r"(b), "r"(c), "r"(d) : "memory");
}
__device__ __forceinline__ void ldg128(uint32_t* r, const char* p) {
    asm volatile("ld.global.v4.u32 {%0,%1,%2,%3}, [%4];" : "=r"(r[0]), "=r"(r[1]), "=r"(r[2]), "=r"(r[3]) : "l"(p) : "memory");
}
__device__ __forceinline__ void ldg64_stream(uint32_t& a, uint32_t& b, const char* p) {
    asm volatile("ld.global.nc.L1::no_allocate.v2.u32 {%0,%1}, [%2];" : "=r"(a), "=r"(b) : "l"(p) : "memory");
}

__device__ __forceinline__ int4 ldg_stream(const int4* p) {
    int4 v;
    asm volatile("ld.global.nc.L1::no_allocate.v4.s32 {%0,%1,%2,%3}, [%4];" : "=r"(v.x), "=r"(v.y), "=r"(v.z), "=r"(v.w) : "l"(p) : "memory");
    return v;
}

__device__ __forceinline__ void mma_k16(float* d, uint32_t a0, uint32_t a1, uint32_t a2, uint32_t a3, uint32_t b0, uint32_t b1,
                                        float c0, float c1, float c2, float c3) {
    asm volatile("mma.sync.aligned.m16n8k16.row.col.f32.bf16.bf16.f32 {%0,%1,%2,%3}, {%4,%5,%6,%7}, {%8,%9}, {%10,%11,%12,%13};"
                 : "=f"(d[0]), "=f"(d[1]), "=f"(d[2]), "=f"(d[3])
                 : "r"(a0), "r"(a1), "r"(a2), "r"(a3), "r"(b0), "r"(b1), "f"(c0), "f"(c1), "f"(c2), "f"(c3));
}
__device__ __forceinline__ uint64_t desc_sw128(uint32_t saddr) {
    return (uint64_t)((saddr & 0x3FFFF) >> 4) | (1ull << 16) | (64ull << 32) | (1ull << 62);
}
template <int SCALE_D>
__device__ __forceinline__ void wgmma_n80(float (&d)[40], uint64_t da, uint64_t db) {
    asm volatile(
        "wgmma.mma_async.sync.aligned.m64n80k16.f32.bf16.bf16 "
        "{%0,%1,%2,%3,%4,%5,%6,%7,%8,%9,%10,%11,%12,%13,%14,%15,"
        "%16,%17,%18,%19,%20,%21,%22,%23,%24,%25,%26,%27,%28,%29,%30,%31,"
        "%32,%33,%34,%35,%36,%37,%38,%39}, "
        "%40, %41, %42, 1, 1, 1, 0;"
        : "+f"(d[0]), "+f"(d[1]), "+f"(d[2]), "+f"(d[3]), "+f"(d[4]), "+f"(d[5]), "+f"(d[6]), "+f"(d[7]),
          "+f"(d[8]), "+f"(d[9]), "+f"(d[10]), "+f"(d[11]), "+f"(d[12]), "+f"(d[13]), "+f"(d[14]), "+f"(d[15]),
          "+f"(d[16]), "+f"(d[17]), "+f"(d[18]), "+f"(d[19]), "+f"(d[20]), "+f"(d[21]), "+f"(d[22]), "+f"(d[23]),
          "+f"(d[24]), "+f"(d[25]), "+f"(d[26]), "+f"(d[27]), "+f"(d[28]), "+f"(d[29]), "+f"(d[30]), "+f"(d[31]),
          "+f"(d[32]), "+f"(d[33]), "+f"(d[34]), "+f"(d[35]), "+f"(d[36]), "+f"(d[37]), "+f"(d[38]), "+f"(d[39])
        : "l"(da), "l"(db), "n"(SCALE_D));
}
__device__ __forceinline__ void node_gemm(float (&d)[40], uint32_t wa, uint32_t xa) {
    const uint64_t da = desc_sw128(wa), db = desc_sw128(xa);
    wgmma_n80<0>(d, da, db);
    wgmma_n80<1>(d, da + 128, db + 2);
    wgmma_n80<1>(d, da + 256, db + 4);
    wgmma_n80<1>(d, da + 384, db + 6);
}
template <int NREG>
__device__ __forceinline__ void reg_fence(float (&d)[NREG]) {
    #pragma unroll
    for (int i = 0; i < NREG; i++) asm volatile("" : "+f"(d[i]) :: "memory");
}

__device__ __forceinline__ uint32_t pack_bf16(float lo, float hi) {
    uint32_t d; asm("cvt.rn.bf16x2.f32 %0, %1, %2;" : "=r"(d) : "f"(hi), "f"(lo)); return d;
}
__device__ __forceinline__ uint32_t fma_bf2(uint32_t a, uint32_t b, uint32_t c) {
    uint32_t d; asm("fma.rn.bf16x2 %0, %1, %2, %3;" : "=r"(d) : "r"(a), "r"(b), "r"(c)); return d;
}
__device__ __forceinline__ uint32_t add_bf2(uint32_t a, uint32_t b) {
    uint32_t d; asm("add.rn.bf16x2 %0, %1, %2;" : "=r"(d) : "r"(a), "r"(b)); return d;
}
__device__ __forceinline__ float ex2f(float x) {
    float y; asm("ex2.approx.ftz.f32 %0, %1;" : "=f"(y) : "f"(x)); return y;
}
__device__ __forceinline__ uint32_t fma_relu_bf2(uint32_t a, uint32_t b, uint32_t c) {
    uint32_t d; asm("fma.rn.relu.bf16x2 %0, %1, %2, %3;" : "=r"(d) : "r"(a), "r"(b), "r"(c)); return d;
}
__device__ __forceinline__ uint32_t gate_pair(float y0, float y1, uint32_t neb, uint32_t niea) {
    const uint32_t na = fma_bf2(pack_bf16(ex2f(y0), ex2f(y1)), neb, niea);
    const uint32_t r0 = ~na;
    const uint32_t e  = fma_relu_bf2(na, r0, 0x40EF40EFu);
    return fma_bf2(r0, e, r0);
}

__device__ __forceinline__ uint4 ld_relaxed_128(const uint4* p) {
    unsigned __int128 t;
    asm volatile("ld.relaxed.gpu.global.b128 %0, [%1];" : "=q"(t) : "l"(p) : "memory");
    return make_uint4((uint32_t)t, (uint32_t)(t >> 32), (uint32_t)(t >> 64), (uint32_t)(t >> 96));
}
__device__ __forceinline__ void st_relaxed_128(uint4* p, uint4 v) {
    const unsigned __int128 t = (unsigned __int128)(((uint64_t)v.w << 32) | v.z) << 64 | (((uint64_t)v.y << 32) | v.x);
    asm volatile("st.relaxed.gpu.global.b128 [%0], %1;" :: "l"(p), "q"(t) : "memory");
}
__device__ __forceinline__ void sts32(uint32_t addr, uint32_t a) { asm volatile("st.shared.u32 [%0], %1;" :: "r"(addr), "r"(a) : "memory"); }
__device__ __forceinline__ uint32_t atoms_inc_if(uint32_t addr, bool p, uint32_t dflt) {
    uint32_t r = dflt;
    asm volatile("{\n\t.reg .pred p;\n\tsetp.ne.u32 p, %2, 0;\n\t@p atom.shared.add.u32 %0, [%1], 1;\n\t}"
                 : "+r"(r) : "r"(addr), "r"((uint32_t)p) : "memory");
    return r;
}
__device__ __forceinline__ uint32_t atoms_inc(uint32_t addr) {
    uint32_t r; asm volatile("atom.shared.add.u32 %0, [%1], 1;" : "=r"(r) : "r"(addr) : "memory"); return r;
}

__global__ void __launch_bounds__(NTHREADS, 1)
gatedgcn_kernel(const __nv_bfloat16* __restrict__ x, const __nv_bfloat16* __restrict__ e_attr,
                const int* __restrict__ src, const int* __restrict__ dst,
                const __nv_bfloat16* __restrict__ w_a, const __nv_bfloat16* __restrict__ w_b,
                const __nv_bfloat16* __restrict__ w_c, const __nv_bfloat16* __restrict__ w_u,
                const __nv_bfloat16* __restrict__ w_v, __nv_bfloat16* __restrict__ out) {
    extern __shared__ __align__(1024) unsigned char smem[];
    const uint32_t sb = (uint32_t)__cvta_generic_to_shared(smem);
    const int tid = threadIdx.x, lane = tid & 31;
    const int warp = uni(tid >> 5);
    const int cta = blockIdx.x;
    const int node0 = cta * NPB;
    const int g = lane >> 2, q = lane & 3;

    int* s_cnt  = (int*)(smem + SM_CNT);
    int* s_ncnt = (int*)(smem + SM_NCNT);
    volatile int* s_misc = (volatile int*)(smem + SM_MISC);

    auto load_weights = [&](int t, int nt) {
        #pragma unroll 1
        for (int i = t; i < 512; i += nt) {
            const uint32_t so = sb + SM_W + (i >> 3) * 128 + (((i ^ (i >> 3)) & 7) << 4);
            cp_async16(so + WS_B, w_b + i * 8);
            cp_async16(so + WS_V, w_v + i * 8);
            cp_async16(so + WS_A, w_a + i * 8);
            cp_async16(so + WS_U, w_u + i * 8);
        }
        if (t < 128) cp_async16(sb + SM_W + WS_C + (t >> 3) * 128 + (((t ^ (t >> 3)) & 7) << 4), w_c + t * 8);
    };

    auto store_rows = [&](const float (&d)[40], uint32_t base, int ld) {
        base += ((lane & 7) + ((lane >> 4) << 3)) * ld + ((warp & 3) * 16 + ((lane >> 3) & 1) * 8) * 2;
        #pragma unroll
        for (int w = 0; w < 10; w += 2)
            stsm_x4_t(base + w * 8 * ld,
                      pack_bf16(d[4 * w + 0], d[4 * w + 1]), pack_bf16(d[4 * w + 2], d[4 * w + 3]),
                      pack_bf16(d[4 * w + 4], d[4 * w + 5]), pack_bf16(d[4 * w + 6], d[4 * w + 7]));
    };
    auto neg_exp = [&](float (&d)[40], float scale, int slot) {
        float mx = 0.f;
        #pragma unroll
        for (int i = 0; i < 40; i++) { mx = fmaxf(mx, fabsf(d[i])); d[i] = -ex2f(d[i] * scale); }
        const uint32_t mb = __reduce_max_sync(0xffffffffu, __float_as_uint(mx));
        if (lane == 0) atomicMax((unsigned int*)&s_misc[slot], mb);
    };

    PROF(0);
    if (warp < NET / 32) {
        const int ebase = cta * CHUNK;
        const int nvec = (min(CHUNK, N_EDGES - ebase)) >> 2;
        int4 dv[4], sv[4];
        bool has[4];
        #pragma unroll
        for (int k = 0; k < 4; k++) {
            const int o = tid + (k & 1) * NET, v = (k >> 1) * WVEC + o;
            has[k] = o < WVEC && v < nvec;
            if (k >= 2) has[k] = has[k] && (dv[0].x | sv[0].x | (has[1] ? dv[1].x | sv[1].x : 0)) >= 0;
            if (has[k]) {
                dv[k] = ldg_stream((const int4*)(dst + ebase) + v);
                sv[k] = ldg_stream((const int4*)(src + ebase) + v);
            }
        }
        if (tid < 272 + 80 + 4 && tid != 272 + 80) s_cnt[tid] = 0;
        const int sg = tid / UMAIN, su = tid - sg * UMAIN;
        const bool act = sg < SPP, act_last = sg + (UPT - 1) * SPP < NB;
        uint32_t tag = 0;
        #pragma unroll
        for (int w = 0; w < 2; w++) {
            bar_sync(1, NET);
            #pragma unroll
            for (int k = 2 * w; k < 2 * w + 2; k++) {
                if (has[k]) {
                    const int v = w * WVEC + tid + (k & 1) * NET;
                    const int dd[4] = {dv[k].x, dv[k].y, dv[k].z, dv[k].w};
                    const int ss[4] = {sv[k].x, sv[k].y, sv[k].z, sv[k].w};
                    uint32_t b[4], rank[4];
                    #pragma unroll
                    for (int j = 0; j < 4; j++) { b[j] = (uint32_t)dd[j] / NPB; rank[j] = (uint32_t)atomicAdd(&s_cnt[w * 136 + b[j]], 1); }
                    #pragma unroll
                    for (int j = 0; j < 4; j++) {
                        const uint32_t rec = (((uint32_t)(v * 4 + j) - b[j]) * NPB + (uint32_t)dd[j]) * N_NODES + (uint32_t)ss[j];
                        sts32(sb + SM_STAGE + (b[j] * SEG_LD + min(rank[j], (uint32_t)SEGCAP)) * 4, rec);
                    }
                }
            }
            if (w == 0) { bar_sync(8, NET + 32); tag = (((uint32_t)s_misc[0] + 1u) & 0xFFFFFFu) << 8; }
            else bar_sync(1, NET);
            PROF(1 + w);
            if (act) {
                const uint32_t a = sb + SM_STAGE + (sg * SEG_LD + 3 * su) * 4;
                uint4* gq = g_seg + (size_t)w * 2 * TAIL + ((size_t)sg * NB + cta) * UMAIN + su;
                uint32_t tmask = 0;
                uint4 pu[UPT];
                #pragma unroll
                for (int k = 0; k < UPT; k++) {
                    const bool on = k < UPT - 1 || act_last;
                    const int cnt = on ? s_cnt[w * 136 + sg + k * SPP] : 0;
                    const uint32_t ak = on ? a + k * SPP * SEG_LD * 4 : a;
                    pu[k] = make_uint4(lds32(ak), lds32(ak + 4), lds32(ak + 8),
                        tag | (cnt > SEGCAP ? 8u : cnt > 3 * (UMAIN + su) ? 4u : 0u) | (uint32_t)min(max(cnt - 3 * su, 0), 3));
                    if (cnt > 3 * (UMAIN + (su & ~1)) && cnt <= SEGCAP) tmask |= 1u << k;
                }
                #pragma unroll
                for (int k = 0; k < UPT; k++)
                    if (k < UPT - 1 || act_last) st_relaxed_128(gq + (size_t)k * SPP * NB * UMAIN, pu[k]);
                while (tmask) {
                    const int k = __ffs(tmask) - 1;
                    tmask &= tmask - 1;
                    const uint32_t ta = a + (k * SPP * SEG_LD + 3 * UMAIN) * 4;
                    const int n = min(max(s_cnt[w * 136 + sg + k * SPP] - 3 * (UMAIN + su), 0), 3);
                    st_relaxed_128(gq + (size_t)k * SPP * NB * UMAIN + TAIL, make_uint4(lds32(ta), lds32(ta + 4), lds32(ta + 8), tag | (uint32_t)n));
                }
            }
        }
        PROF(3);
        const uint4* gp = g_seg + (size_t)cta * NB * UMAIN + tid;
        const uint32_t dcnt = sb + SM_DCNT + lane * 4, dump = sb + SM_DUMP + lane * 8 - CAPN * 8;
        uint4 rec[2 * UPT];
        auto fetch = [&](int w) {
            #pragma unroll
            for (int k = 0; k < UPT; k++) {
                rec[w * UPT + k].w = tag;
                if (k < UPT - 1 ? act : act_last) rec[w * UPT + k] = ld_relaxed_128(gp + w * 2 * TAIL + k * SPP * UMAIN);
            }
        };
        fetch(0);
        bar_sync(3, NTHREADS);
        PROF(4);
        bool first = true;
        uint32_t todo = 3;
        #pragma unroll 1
        while (todo) {
            #pragma unroll
            for (int w = 0; w < 2; w++) {
                if (!(todo >> w & 1)) continue;
                bool more = false;
                for (int tries = 0;; tries++) {
                    bool ok = true;
                    #pragma unroll
                    for (int k = 0; k < UPT; k++)
                        if ((rec[w * UPT + k].w ^ tag) >> 8) { rec[w * UPT + k] = ld_relaxed_128(gp + w * 2 * TAIL + k * SPP * UMAIN); ok = false; }
                    if (__all_sync(0xffffffffu, ok)) break;
                    if (tries > 400000) {
                        s_misc[1] = 1;
                        #pragma unroll
                        for (int k = 0; k < UPT; k++) rec[w * UPT + k].w = tag;
                    }
                }
                uint32_t sv_[UPT][3], el[UPT][3], la[UPT][3], r[UPT][3];
                #pragma unroll
                for (int k = 0; k < UPT; k++) {
                    uint4& u = rec[w * UPT + k];
                    const uint32_t rw[3] = {u.x, u.y, u.z}, hdr = u.w;
                    #pragma unroll
                    for (int j = 0; j < 3; j++) {
                        const uint32_t t = rw[j] / N_NODES;
                        el[k][j] = t / NPB;
                        const uint32_t dl = t - el[k][j] * NPB;
                        sv_[k][j] = (rw[j] - t * N_NODES) << 8;
                        const bool valid = j < (int)(hdr & 3);
                        la[k][j] = valid ? sb + SM_LIST + dl * LIST_LD : dump;
                        r[k][j] = atoms_inc(valid ? sb + SM_NCNT + dl * 4 : dcnt);
                    }
                    if (hdr & 8) s_misc[1] = 1;
                    u.w = tag;
                    if (hdr & 4) { u = ld_relaxed_128(gp + w * 2 * TAIL + k * SPP * UMAIN + TAIL); more = true; }
                }
                if (!__any_sync(0xffffffffu, more)) todo &= ~(1u << w);

                #pragma unroll
                for (int k = 0; k < UPT; k++)
                    #pragma unroll
                    for (int j = 0; j < 3; j++)
                        sts64(la[k][j] + min(r[k][j], (uint32_t)CAPN) * 8, sv_[k][j], ((sg + k * SPP) * CHUNK + el[k][j]) * 32u);
                if (w == 0 && first) { fetch(1); first = false; }
            }
            gp += TAIL;
        }
        PROF(5);
    } else {
        const int wtid = tid - NET;
        uint32_t epoch = 0;
        if (wtid == 96) epoch = *(volatile unsigned int*)&g_epoch[cta * 8];
        {
            const uint32_t so = (wtid >> 3) * 128 + (((wtid ^ (wtid >> 3)) & 7) << 4);
            #pragma unroll
            for (int k = 0; k < 5; k++) {
                const int r = (wtid >> 3) + 16 * k;
                const bool ok = r < NPB && node0 + r < N_NODES;
                cp_async16_zfill(sb + SM_XOWN + so + k * 2048, x + (ok ? (size_t)node0 * 64 + wtid * 8 + k * 1024 : 0), ok ? 16 : 0);
            }
            #pragma unroll
            for (int k = 0; k < 4; k++) {
                cp_async16(sb + SM_W + WS_V + so + k * 2048, w_v + wtid * 8 + k * 1024);
                cp_async16(sb + SM_W + WS_B + so + k * 2048, w_b + wtid * 8 + k * 1024);
            }
            cp_commit();
            #pragma unroll
            for (int k = 0; k < 4; k++) {
                cp_async16(sb + SM_W + WS_A + so + k * 2048, w_a + wtid * 8 + k * 1024);
                cp_async16(sb + SM_W + WS_U + so + k * 2048, w_u + wtid * 8 + k * 1024);
            }
            cp_async16(sb + SM_W + WS_C + so, w_c + wtid * 8);
            cp_commit();
        }
        if (wtid >= 96) {
            if (lane == 0) { s_misc[0] = (int)epoch; g_epoch[cta * 8] = epoch + 1u; }
            __syncwarp();
            bar_arrive(8, NET + 32);
        }
        if (wtid < 8) sts128(sb + SM_LIST + NULLT + wtid * 16, NULL_W0, 0u, NULL_W0, 0u);
        if (wtid >= 8 && wtid < 12) s_misc[wtid - 4] = 0;
        if (wtid >= 32 && wtid < 96) s_misc[wtid - 24] = wtid < 64 ? 0 : CAPN;
        cp_wait<1>();
        fence_async();
        bar_sync(2, 128);
        {
            float db[40], dv[40];
            wgmma_fence();
            node_gemm(dv, sb + SM_W + WS_V, sb + SM_XOWN);
            wgmma_commit();
            node_gemm(db, sb + SM_W + WS_B, sb + SM_XOWN);
            wgmma_commit();
            wgmma_wait<1>();
            reg_fence(dv);
            store_rows(dv, sb + SM_T + 128, T_LD);
            float mv = 0.f;
            #pragma unroll
            for (int i = 0; i < 40; i++) mv = fmaxf(mv, fabsf(dv[i]));
            if (mv > 1e9f) s_misc[5] = 0x7F800000;
            wgmma_wait<0>();
            reg_fence(db);
            neg_exp(db, -L2E, 5);
            store_rows(db, sb + SM_T, T_LD);
        }
        bar_sync(2, 128);
        {
            uint4 v[10];
            #pragma unroll
            for (int k = 0; k < 10; k++)
                v[k] = lds128(sb + SM_T + ((wtid >> 4) + 8 * k) * T_LD + (wtid & 1) * 128 + ((wtid >> 1) & 7) * 16);
            #pragma unroll
            for (int k = 0; k < 10; k++) {
                const int r = (wtid >> 4) + 8 * k;
                if (node0 + r == N_NODES) v[k].x = v[k].y = v[k].z = v[k].w = (wtid & 1) ? 0u : 0xFF80FF80u;
                if (r < NPB && node0 + r <= N_NODES) g_tab[(size_t)node0 * 16 + wtid + k * 128] = v[k];
            }
        }
        cp_wait<0>();
        fence_async();
        bar_arrive(3, NTHREADS);
        bar_sync(2, 128);
        PROFG(12);
        const uint32_t ftag = (uint32_t)s_misc[0] + 1u;
        {
            float da[40], du[40];
            wgmma_fence();
            node_gemm(du, sb + SM_W + WS_U, sb + SM_XOWN);
            node_gemm(da, sb + SM_W + WS_A, sb + SM_XOWN);
            wgmma_commit();
            if (wtid == 96)
                asm volatile("st.release.gpu.global.u64 [%0], %1;"
                             :: "l"(&g_flag[cta]), "l"(((unsigned long long)ftag << 32) | (uint32_t)s_misc[5]) : "memory");
            __syncwarp();
            wgmma_wait<0>();
            reg_fence(du);
            reg_fence(da);
            store_rows(du, sb + SM_U, U_LD);
            neg_exp(da, L2E, 4);
            store_rows(da, sb + SM_IEA, U_LD);
        }
        if (wtid < 96) {
            #pragma unroll 2
            for (int i = wtid; i < 512; i += 96) {
                const int l = i >> 4, j = (i >> 1) & 7, h = i & 1;
                const int f = 32 * (j >> 2) + 8 * (l >> 3) + 2 * (j & 3) + ((l >> 2) & 1);
                const int r = 4 * (l & 3) + 2 * h;
                const unsigned char* wc = smem + SM_W + WS_C + (f & 7) * 2;
                const float c0 = __bfloat162float(*(const __nv_bfloat16*)(wc + r * 128 + (((f >> 3) ^ (r & 7)) << 4)));
                const float c1 = __bfloat162float(*(const __nv_bfloat16*)(wc + (r + 1) * 128 + (((f >> 3) ^ ((r + 1) & 7)) << 4)));
                ((uint32_t*)(smem + SM_WCF))[((i >> 2) & 3) * 128 + l * 4 + (i & 3)] = pack_bf16(c0 * -L2E, c1 * -L2E);
            }
            uint4 f = make_uint4(0u, ftag, 0u, ftag);
            for (int tries = 0;; tries++) {
                if (wtid < NB / 2)
                    asm volatile("ld.acquire.gpu.global.v4.u32 {%0,%1,%2,%3}, [%4];"
                                 : "=r"(f.x), "=r"(f.y), "=r"(f.z), "=r"(f.w) : "l"((const uint4*)g_flag + wtid) : "memory");
                if (__all_sync(0xffffffffu, f.y == ftag && f.w == ftag)) break;
                if (tries > 100000) { f.x = 0x7F800000u; break; }
            }
            const uint32_t mx = __reduce_max_sync(0xffffffffu, max(f.x, f.z));
            if (lane == 0) atomicMax((unsigned int*)&s_misc[6], mx);
            PROFG(11);
        }
    }
    __syncthreads();
    PROF(6);
    const bool bad_list = s_misc[1] != 0 ||
        __any_sync(0xffffffffu, max(max(s_ncnt[lane], s_ncnt[lane + 32]), s_ncnt[min(lane + 64, NPB - 1)]) > CAPN);

    auto reduce_rows = [&](float (&sum)[4], const uint32_t (&den)[8], const uint32_t (&num)[8]) {
        float s1[4] = {0.f, 0.f, 0.f, 0.f}, s2[4] = {0.f, 0.f, 0.f, 0.f};
        uint32_t ln;
        asm volatile("mov.u32 %0, %%laneid;" : "=r"(ln));
        #pragma unroll
        for (int j = 0; j < 4; j++) {
            const uint32_t sel = ((ln >> 2) & 3) == j ? 0x3F803F80u : 0u;
            mma_k16(s1, sel, 0u, 0u, sel, movm(den[j]), movm(num[j]), s1[0], s1[1], s1[2], s1[3]);
            mma_k16(s2, sel, 0u, 0u, sel, movm(den[j + 4]), movm(num[j + 4]), s2[0], s2[1], s2[2], s2[3]);
        }
        #pragma unroll
        for (int i = 0; i < 4; i++) sum[i] = ln < 16 ? s1[i] : s2[i];
    };
    auto write_node = [&](int node, const float (&sum)[4], int f0) {
        if (node0 + node < N_NODES) {
            const uint32_t iw = lds32(sb + SM_IEA + node * U_LD + f0 * 2);
            const uint32_t uw = lds32(sb + SM_U + node * U_LD + f0 * 2);
            const uint32_t xw = lds32(sb + SM_XOWN + node * 128 + (((f0 >> 3) ^ (node & 7)) << 4) + (f0 & 7) * 2);
            const float i0 = __uint_as_float(iw << 16), i1 = __uint_as_float(iw & 0xFFFF0000u);
            const float z0 = __uint_as_float(uw << 16) + __fdividef(sum[2] * i0, sum[0] * i0 - RSCALE * 1e-6f);
            const float z1 = __uint_as_float(uw & 0xFFFF0000u) + __fdividef(sum[3] * i1, sum[1] * i1 - RSCALE * 1e-6f);
            const float o0 = __uint_as_float(xw << 16) + fmaxf(z0, 0.f);
            const float o1 = __uint_as_float(xw & 0xFFFF0000u) + fmaxf(z1, 0.f);
            *(uint32_t*)(out + (size_t)(node0 + node) * 64 + f0) = pack_bf16(o0, o1);
        }
    };
    const char* eq = (const char*)e_attr + q * 8;
    const uint32_t la = sb + SM_LIST + g * 8;
    const bool fast = !bad_list && __int_as_float(s_misc[4]) + __int_as_float(s_misc[6]) <= RANGE_MAX;

    if (fast) {
        auto job_range = [&](int j, int& tb, int& te) {
            tb = NULLT; te = NULLT + 128;
            if (j >= NJOBS) return -1;
            const int n = j < NWHOLE ? j : NWHOLE + ((j - NWHOLE) >> 1);
            const int cnt = s_ncnt[n];
            const int nt = max(1, (cnt + 15) >> 4);
            if (cnt + lane < nt * 16) sts64(sb + SM_LIST + n * LIST_LD + (cnt + lane) * 8, NULL_W0, 0u);
            __syncwarp();
            const int mid = j < NWHOLE ? nt : (nt + 1) >> 1;
            const bool second = j >= NWHOLE && ((j - NWHOLE) & 1);
            if (!second) { tb = n * LIST_LD; te = tb + mid * 128; }
            else if (mid < nt) { tb = n * LIST_LD + mid * 128; te = n * LIST_LD + nt * 128; }
            return n;
        };
        const char* tabq = (const char*)g_tab + q * 32;
        asm volatile("" : "+l"(tabq));
        uint32_t wcf[16];
        #pragma unroll
        for (int i = 0; i < 4; i++) {
            const uint4 v = lds128(sb + SM_WCF + i * 512 + lane * 16);
            wcf[4 * i] = v.x; wcf[4 * i + 1] = v.y; wcf[4 * i + 2] = v.z; wcf[4 * i + 3] = v.w;
        }
        uint32_t eb[2][8], hq[2][8], ev[4];
        const char *p0, *p1;
        bool v0, v1;
        auto load_rec = [&](int tt) {
            const uint2 r0 = lds64(la + tt), r1 = lds64(la + tt + 64);
            p0 = tabq + r0.x; p1 = tabq + r1.x;
            v0 = r0.x != NULL_W0; v1 = r1.x != NULL_W0;
            ldg64_stream(ev[0], ev[2], eq + r0.y);
            ldg64_stream(ev[1], ev[3], eq + r1.y);
        };
        auto load_half = [&](int h) {
            ldg128(&eb[0][4 * h], p0 + 128 * h); ldg128(&eb[1][4 * h], p1 + 128 * h);
            ldg128(&hq[0][4 * h], p0 + 16 + 128 * h); ldg128(&hq[1][4 * h], p1 + 16 + 128 * h);
        };
        auto load_rows = [&]() { load_half(0); load_half(1); };
        const int yes = s_misc[1] == 0;
        int t, te;
        int node = job_range(warp, t, te);
        load_rec(t);
        load_rows();
        PROF(15);
        while (true) {
            int nnode = 0;
            uint32_t iea[8], den[8], num[8];
            {
                const uint4 w0 = lds128(sb + SM_IEA + node * U_LD + q * 16), w1 = lds128(sb + SM_IEA + node * U_LD + 64 + q * 16);
                iea[0] = w0.x; iea[1] = w0.y; iea[2] = w0.z; iea[3] = w0.w; iea[4] = w1.x; iea[5] = w1.y; iea[6] = w1.z; iea[7] = w1.w;
            }
            #pragma unroll
            for (int j = 0; j < 8; j++) { den[j] = 0u; num[j] = 0u; }
            bool last;
            do {
                const uint32_t a0 = v0 ? ev[0] : 0u, a1 = v1 ? ev[1] : 0u, a2 = v0 ? ev[2] : 0u, a3 = v1 ? ev[3] : 0u;
                t += 128;
                last = t == te;
                if (last) nnode = job_range(uni((int)atoms_inc_if(sb + SM_MISC + 12, lane == 0, 0u)) + NWARPS, t, te);
                load_rec(t);
                #pragma unroll
                for (int h = 0; h < 2; h++) {
                    if (h == 1) { int y = yes; asm volatile("" : "+r"(y) :: "memory"); if (!y) break; }
                    float d[16];
                    #pragma unroll
                    for (int j = 0; j < 4; j++)
                        mma_k16(&d[4 * j], a0, a1, a2, a3, wcf[8 * h + 2 * j], wcf[8 * h + 2 * j + 1], 0.f, 0.f, 0.f, 0.f);
                    #pragma unroll
                    for (int jj = 0; jj < 4; jj++) {
                        const int j = 4 * h + jj;
                        const uint32_t ra = gate_pair(d[4 * jj], d[4 * jj + 1], eb[0][j], iea[j]);
                        const uint32_t rb = gate_pair(d[4 * jj + 2], d[4 * jj + 3], eb[1][j], iea[j]);
                        den[j] = add_bf2(add_bf2(den[j], ra), rb);
                        num[j] = fma_bf2(rb, hq[1][j], fma_bf2(ra, hq[0][j], num[j]));
                    }
                    load_half(h);
                }
            } while (!last);
            const int f0 = 32 * (g >> 2) + 8 * q + 2 * (g & 3);
            float sum[4];
            reduce_rows(sum, den, num);
            bool mine = true;
            if (node >= NWHOLE) {
                const uint32_t st = sb + SM_STATE + (node - NWHOLE) * 4, pa = sb + SM_PART + (node - NWHOLE) * 512 + lane * 16;
                mine = uni((int)atoms_inc_if(st, lane == 0, 0u)) != 0;
                if (!mine) {
                    sts128(pa, __float_as_uint(sum[0]), __float_as_uint(sum[1]), __float_as_uint(sum[2]), __float_as_uint(sum[3]));
                    __threadfence_block();
                    __syncwarp();
                    if (lane == 0) atomicAdd((int*)(smem + (st - sb)), 2);
                } else {
                    while (*(volatile int*)(smem + (st - sb)) < 4) {}
                    __threadfence_block();
                    const uint4 o = lds128(pa);
                    sum[0] += __uint_as_float(o.x); sum[1] += __uint_as_float(o.y);
                    sum[2] += __uint_as_float(o.z); sum[3] += __uint_as_float(o.w);
                }
            }
            if (mine) write_node(node, sum, f0);
            if (nnode < 0) break;
            node = nnode;
        }
        PROFE();
    } else {
        float2* acc = g_acc + (size_t)cta * NPB * 64;
        __syncthreads();
        load_weights(tid, NTHREADS);
        cp_commit();
        for (int i = tid; i < NPB * 64; i += NTHREADS) acc[i] = make_float2(0.f, 0.f);
        cp_wait<0>();
        int scan_pos = bad_list ? 0 : N_EDGES;
        int pend = 0, pv = 0;
        int4 d4 = make_int4(0, 0, 0, 0);
        bool more = true;
        while (more) {
            if (bad_list) {
                __syncthreads();
                if (tid < 80) s_ncnt[tid] = 0;
                __syncthreads();
                while (true) {
                    const int dd[4] = {d4.x, d4.y, d4.z, d4.w};
                    #pragma unroll
                    for (int j = 0; j < 4; j++) {
                        if (pend >> j & 1) {
                            const int dl = dd[j] - node0;
                            const int r = atomicAdd(&s_ncnt[dl], 1);
                            if (r < CAPN) {
                                const int e = pv * 4 + j;
                                sts64(sb + SM_LIST + dl * LIST_LD + r * 8, (uint32_t)__ldg(src + e) << 8, (uint32_t)e * 32u);
                                pend &= ~(1 << j);
                            }
                        }
                    }
                    if (__syncthreads_or(pend)) break;
                    if (scan_pos >= N_EDGES) { more = false; break; }
                    pv = (scan_pos >> 2) + tid;
                    if (pv < N_EDGES / 4) {
                        d4 = __ldg((const int4*)dst + pv);
                        pend = ((uint32_t)(d4.x - node0) < NPB ? 1 : 0) | ((uint32_t)(d4.y - node0) < NPB ? 2 : 0)
                             | ((uint32_t)(d4.z - node0) < NPB ? 4 : 0) | ((uint32_t)(d4.w - node0) < NPB ? 8 : 0);
                    }
                    scan_pos += NTHREADS * 4;
                }
            } else {
                more = false;
                __syncthreads();
            }
            const uint32_t wrow = sb + SM_W + (lane & 15) * 128;
            #pragma unroll 1
            for (int job = warp; job < NPB * 4; job += NWARPS) {
                const int n = job >> 2, jp = job & 3;
                const int cnt = min(s_ncnt[n], CAPN);
                if (cnt == 0) continue;
                const uint32_t wa = wrow + (((2 * jp + (lane >> 4)) ^ (lane & 7)) << 4);
                float ca[8] = {0.f, 0.f, 0.f, 0.f, 0.f, 0.f, 0.f, 0.f};
                #pragma unroll
                for (int k = 0; k < 4; k++) {
                    const uint32_t a0 = lds32(sb + SM_XOWN + n * 128 + (((2 * k) ^ (n & 7)) << 4) + q * 4);
                    const uint32_t a2 = lds32(sb + SM_XOWN + n * 128 + (((2 * k + 1) ^ (n & 7)) << 4) + q * 4);
                    uint32_t b[4];
                    ldsm_x4_t(b, wa + WS_A + k * 2048);
                    mma_k16(&ca[0], a0, a0, a2, a2, b[0], b[1], ca[0], ca[1], ca[2], ca[3]);
                    mma_k16(&ca[4], a0, a0, a2, a2, b[2], b[3], ca[4], ca[5], ca[6], ca[7]);
                }
                float sd[4] = {0.f, 0.f, 0.f, 0.f}, sn[4] = {0.f, 0.f, 0.f, 0.f};
                #pragma unroll 1
                for (int i0 = 0; i0 < cnt; i0 += 16) {
                    const bool v0 = i0 + g < cnt, v1 = i0 + g + 8 < cnt;
                    const uint2 r0 = lds64(sb + SM_LIST + n * LIST_LD + (v0 ? i0 + g : 0) * 8);
                    const uint2 r1 = lds64(sb + SM_LIST + n * LIST_LD + (v1 ? i0 + g + 8 : 0) * 8);
                    const uint32_t* x0 = (const uint32_t*)((const char*)x + (r0.x >> 1)) + q;
                    const uint32_t* x1 = (const uint32_t*)((const char*)x + (r1.x >> 1)) + q;
                    const uint32_t* e0 = (const uint32_t*)((const char*)e_attr + r0.y) + q;
                    const uint32_t* e1 = (const uint32_t*)((const char*)e_attr + r1.y) + q;
                    float gg[8], hh[8] = {0.f, 0.f, 0.f, 0.f, 0.f, 0.f, 0.f, 0.f};
                    uint32_t b[4];
                    {
                        const uint32_t a0 = __ldg(e0), a1 = __ldg(e1), a2 = __ldg(e0 + 4), a3 = __ldg(e1 + 4);
                        ldsm_x4_t(b, wa + WS_C);
                        mma_k16(&gg[0], a0, a1, a2, a3, b[0], b[1], ca[0], ca[1], ca[2], ca[3]);
                        mma_k16(&gg[4], a0, a1, a2, a3, b[2], b[3], ca[4], ca[5], ca[6], ca[7]);
                    }
                    #pragma unroll
                    for (int k = 0; k < 4; k++) {
                        const uint32_t a0 = __ldg(x0 + 8 * k), a1 = __ldg(x1 + 8 * k), a2 = __ldg(x0 + 8 * k + 4), a3 = __ldg(x1 + 8 * k + 4);
                        ldsm_x4_t(b, wa + WS_B + k * 2048);
                        mma_k16(&gg[0], a0, a1, a2, a3, b[0], b[1], gg[0], gg[1], gg[2], gg[3]);
                        mma_k16(&gg[4], a0, a1, a2, a3, b[2], b[3], gg[4], gg[5], gg[6], gg[7]);
                        ldsm_x4_t(b, wa + WS_V + k * 2048);
                        mma_k16(&hh[0], a0, a1, a2, a3, b[0], b[1], hh[0], hh[1], hh[2], hh[3]);
                        mma_k16(&hh[4], a0, a1, a2, a3, b[2], b[3], hh[4], hh[5], hh[6], hh[7]);
                    }
                    #pragma unroll
                    for (int i = 0; i < 8; i++) {
                        const float eta = ((i & 2) ? v1 : v0) ? 1.0f / (1.0f + ex2f(gg[i] * -L2E)) : 0.f;
                        const int o = (i >> 2) * 2 + (i & 1);
                        sd[o] += eta;
                        sn[o] = fmaf(eta, hh[i], sn[o]);
                    }
                }
                #pragma unroll
                for (int i = 0; i < 4; i++) {
                    #pragma unroll
                    for (int o = 4; o < 32; o <<= 1) {
                        sd[i] += __shfl_xor_sync(0xffffffffu, sd[i], o);
                        sn[i] += __shfl_xor_sync(0xffffffffu, sn[i], o);
                    }
                }
                if (g == 0) {
                    #pragma unroll
                    for (int i = 0; i < 4; i++) {
                        float2* pa = acc + n * 64 + jp * 16 + (i >> 1) * 8 + 2 * q + (i & 1);
                        *pa = make_float2(pa->x + sd[i], pa->y + sn[i]);
                    }
                }
            }
        }
        __syncthreads();
        for (int i = tid; i < NPB * 64; i += NTHREADS) {
            const int n = i >> 6, f = i & 63;
            if (node0 + n < N_NODES) {
                const float2 a = acc[i];
                const float u = __bfloat162float(*(const __nv_bfloat16*)(smem + SM_U + n * U_LD + f * 2));
                const float xv = __bfloat162float(*(const __nv_bfloat16*)(smem + SM_XOWN + n * 128 + (((f >> 3) ^ (n & 7)) << 4) + (f & 7) * 2));
                out[(size_t)(node0 + n) * 64 + f] = __float2bfloat16(xv + fmaxf(u + a.y / (a.x + 1e-6f), 0.f));
            }
        }
    }
}

}

extern "C" void kernel_launch(void* const* d_in, const int* in_sizes, int n_in, void* d_out, int out_size) {
    (void)in_sizes; (void)n_in; (void)out_size;
    constexpr int SMEM = SM_TOTAL + 128;
    cudaFuncSetAttribute(gatedgcn_kernel, cudaFuncAttributeMaxDynamicSharedMemorySize, SMEM);
    gatedgcn_kernel<<<NB, NTHREADS, SMEM>>>(
        (const __nv_bfloat16*)d_in[0], (const __nv_bfloat16*)d_in[1], (const int*)d_in[2], (const int*)d_in[3],
        (const __nv_bfloat16*)d_in[4], (const __nv_bfloat16*)d_in[5], (const __nv_bfloat16*)d_in[6],
        (const __nv_bfloat16*)d_in[7], (const __nv_bfloat16*)d_in[8], (__nv_bfloat16*)d_out);
}
```

```cpp
#include <cuda_runtime.h>
#include <cuda_bf16.h>
#include <stdint.h>

namespace {

constexpr int N_NODES  = 10000;
constexpr int N_EDGES  = 640000;
constexpr int NB       = 132;
constexpr int NPB      = 76;
constexpr int CHUNK    = 4864;
constexpr int UMAIN    = 8;
constexpr int SEGCAP   = 7 * UMAIN;
constexpr int WVEC     = CHUNK / 8;
constexpr int SEG_LD   = SEGCAP + 4;
constexpr int CAPN     = 112;
constexpr int LIST_LD  = (CAPN + 1) * 8;
constexpr int NTHREADS = 512;
constexpr int NWARPS   = NTHREADS / 32;
constexpr int NET      = 384;
constexpr int NSPLIT   = 12;
constexpr int NWHOLE   = NPB - NSPLIT;
constexpr int NJOBS    = NWHOLE + 2 * NSPLIT;
constexpr int SPP      = NET / UMAIN;
constexpr int UPT      = (NB + SPP - 1) / SPP;
constexpr int TAIL     = NB * NB * UMAIN;
static_assert(UMAIN % 2 == 0 && NET % UMAIN == 0 && WVEC <= 2 * NET && SEG_LD % 4 == 0, "exchange geometry");
static_assert(NB * NPB > N_NODES && NB * CHUNK >= N_EDGES, "coverage");

constexpr int U_LD = 144;
constexpr int T_LD = 272;

constexpr int SM_XOWN  = 0;
constexpr int SM_LIST  = SM_XOWN + 80 * 128;
constexpr int SM_STAGE = SM_LIST;
constexpr int NULLT    = NPB * LIST_LD;
constexpr int SM_T     = SM_LIST + NULLT - 80 * T_LD;
constexpr int SM_W     = (SM_LIST + NULLT + 128 + 1023) / 1024 * 1024;
constexpr int W_BYTES  = (4 * 64 + 16) * 128;
constexpr int SM_IEA   = SM_W;
constexpr int SM_PART  = SM_W + 16384;
constexpr int SM_U     = SM_W + W_BYTES;
constexpr int SM_WCF   = SM_U + 80 * U_LD;
constexpr int SM_CNT   = SM_WCF + 2048;
constexpr int SM_NCNT  = SM_CNT + 2 * 136 * 4;
constexpr int SM_MISC  = SM_NCNT + 80 * 4;
constexpr int SM_STATE = SM_MISC + 8 * 4;
constexpr int SM_DCNT  = SM_STATE + 32 * 4;
constexpr int SM_DUMP  = SM_DCNT + 32 * 4;
constexpr int SM_TOTAL = SM_DUMP + 32 * 8;
static_assert(SM_STAGE + NB * SEG_LD * 4 <= SM_T && SM_T % 16 == 0, "staging fits");
static_assert(SM_W % 16 == 0 && NULLT % 16 == 0, "alignment");
constexpr uint32_t REC_NONE = 0x7F000000u, REC_OVF = 0x7E000000u;
static_assert((unsigned long long)CHUNK / 2 * NPB * N_NODES <= REC_OVF, "record fits 31 bits");
static_assert(80 * U_LD <= 16384 && NSPLIT <= 32, "aliases fit");
static_assert(SM_TOTAL <= 134144 - 256, "fits the 132 KB carve-out");

constexpr int WS_B = 0, WS_V = 8192, WS_A = 16384, WS_U = 24576, WS_C = 32768;

constexpr uint32_t NULL_W0 = (uint32_t)N_NODES * 256u;
constexpr float L2E = 1.4426950408889634f;
constexpr float RSCALE = 17.906f;
constexpr float RANGE_MAX = 61.0f;

__device__ __align__(128) unsigned int g_epoch[NB * 8];
__device__ __align__(128) unsigned long long g_flag[NB];
__device__ __align__(128) uint4 g_seg[(size_t)4 * NB * NB * UMAIN];
__device__ __align__(256) uint4 g_tab[(size_t)(N_NODES + 1) * 16];
__device__ float2 g_acc[(size_t)NB * NPB * 64];

#define PROFE() do {} while (0)
#define PROF(i) do {} while (0)
#define PROFG(i) do {} while (0)

__device__ __forceinline__ void cp_async16(uint32_t dst, const void* src) {
    asm volatile("cp.async.cg.shared.global [%0], [%1], 16;" :: "r"(dst), "l"(src) : "memory");
}
__device__ __forceinline__ void cp_async16_zfill(uint32_t dst, const void* src, int sz) {
    asm volatile("cp.async.cg.shared.global [%0], [%1], 16, %2;" :: "r"(dst), "l"(src), "r"(sz) : "memory");
}
__device__ __forceinline__ void cp_commit() { asm volatile("cp.async.commit_group;" ::: "memory"); }
template <int N> __device__ __forceinline__ void cp_wait() { asm volatile("cp.async.wait_group %0;" :: "n"(N) : "memory"); }
__device__ __forceinline__ void fence_async() { asm volatile("fence.proxy.async.shared::cta;" ::: "memory"); }
__device__ __forceinline__ void wgmma_fence() { asm volatile("wgmma.fence.sync.aligned;" ::: "memory"); }
__device__ __forceinline__ void wgmma_commit() { asm volatile("wgmma.commit_group.sync.aligned;" ::: "memory"); }
template <int N> __device__ __forceinline__ void wgmma_wait() { asm volatile("wgmma.wait_group.sync.aligned %0;" :: "n"(N) : "memory"); }
__device__ __forceinline__ void bar_sync(int id, int n) { asm volatile("bar.sync %0, %1;" :: "r"(id), "r"(n) : "memory"); }
__device__ __forceinline__ void bar_arrive(int id, int n) { asm volatile("bar.arrive %0, %1;" :: "r"(id), "r"(n) : "memory"); }
__device__ __forceinline__ int uni(int v) { return __shfl_sync(0xffffffffu, v, 0); }

__device__ __forceinline__ void ldsm_x4_t(uint32_t (&r)[4], uint32_t addr) {
    asm volatile("ldmatrix.sync.aligned.m8n8.x4.trans.shared.b16 {%0,%1,%2,%3}, [%4];"
                 : "=r"(r[0]), "=r"(r[1]), "=r"(r[2]), "=r"(r[3]) : "r"(addr) : "memory");
}
__device__ __forceinline__ void stsm_x4_t(uint32_t addr, uint32_t r0, uint32_t r1, uint32_t r2, uint32_t r3) {
    asm volatile("stmatrix.sync.aligned.m8n8.x4.trans.shared.b16 [%0], {%1,%2,%3,%4};"
                 :: "r"(addr), "r"(r0), "r"(r1), "r"(r2), "r"(r3) : "memory");
}
__device__ __forceinline__ uint32_t movm(uint32_t a) {
    uint32_t d; asm volatile("movmatrix.sync.aligned.m8n8.trans.b16 %0, %1;" : "=r"(d) : "r"(a)); return d;
}
__device__ __forceinline__ uint32_t lds32(uint32_t addr) {
    uint32_t v; asm volatile("ld.shared.u32 %0, [%1];" : "=r"(v) : "r"(addr) : "memory"); return v;
}
__device__ __forceinline__ uint2 lds64(uint32_t addr) {
    uint2 v; asm volatile("ld.shared.v2.u32 {%0,%1}, [%2];" : "=r"(v.x), "=r"(v.y) : "r"(addr) : "memory"); return v;
}
__device__ __forceinline__ uint4 lds128(uint32_t addr) {
    uint4 v; asm volatile("ld.shared.v4.u32 {%0,%1,%2,%3}, [%4];" : "=r"(v.x), "=r"(v.y), "=r"(v.z), "=r"(v.w) : "r"(addr) : "memory"); return v;
}
__device__ __forceinline__ void sts64(uint32_t addr, uint32_t a, uint32_t b) {
    asm volatile("st.shared.v2.u32 [%0], {%1,%2};" :: "r"(addr), "r"(a), "r"(b) : "memory");
}
__device__ __forceinline__ void sts128(uint32_t addr, uint32_t a, uint32_t b, uint32_t c, uint32_t d) {
    asm volatile("st.shared.v4.u32 [%0], {%1,%2,%3,%4};" :: "r"(addr), "r"(a), "r"(b), "r"(c), "r"(d) : "memory");
}
__device__ __forceinline__ void ldg128(uint32_t* r, const char* p) {
    asm volatile("ld.global.v4.u32 {%0,%1,%2,%3}, [%4];" : "=r"(r[0]), "=r"(r[1]), "=r"(r[2]), "=r"(r[3]) : "l"(p) : "memory");
}
__device__ __forceinline__ void ldg64_stream(uint32_t& a, uint32_t& b, const char* p) {
    asm volatile("ld.global.nc.L1::no_allocate.v2.u32 {%0,%1}, [%2];" : "=r"(a), "=r"(b) : "l"(p) : "memory");
}

__device__ __forceinline__ int4 ldg_stream(const int4* p) {
    int4 v;
    asm volatile("ld.volatile.global.v4.s32 {%0,%1,%2,%3}, [%4];" : "=r"(v.x), "=r"(v.y), "=r"(v.z), "=r"(v.w) : "l"(p) : "memory");
    return v;
}

__device__ __forceinline__ void mma_k16(float* d, uint32_t a0, uint32_t a1, uint32_t a2, uint32_t a3, uint32_t b0, uint32_t b1,
                                        float c0, float c1, float c2, float c3) {
    asm volatile("mma.sync.aligned.m16n8k16.row.col.f32.bf16.bf16.f32 {%0,%1,%2,%3}, {%4,%5,%6,%7}, {%8,%9}, {%10,%11,%12,%13};"
                 : "=f"(d[0]), "=f"(d[1]), "=f"(d[2]), "=f"(d[3])
                 : "r"(a0), "r"(a1), "r"(a2), "r"(a3), "r"(b0), "r"(b1), "f"(c0), "f"(c1), "f"(c2), "f"(c3));
}
__device__ __forceinline__ uint64_t desc_sw128(uint32_t saddr) {
    return (uint64_t)((saddr & 0x3FFFF) >> 4) | (1ull << 16) | (64ull << 32) | (1ull << 62);
}
template <int SCALE_D>
__device__ __forceinline__ void wgmma_n80(float (&d)[40], uint64_t da, uint64_t db) {
    asm volatile(
        "wgmma.mma_async.sync.aligned.m64n80k16.f32.bf16.bf16 "
        "{%0,%1,%2,%3,%4,%5,%6,%7,%8,%9,%10,%11,%12,%13,%14,%15,"
        "%16,%17,%18,%19,%20,%21,%22,%23,%24,%25,%26,%27,%28,%29,%30,%31,"
        "%32,%33,%34,%35,%36,%37,%38,%39}, "
        "%40, %41, %42, 1, 1, 1, 0;"
        : "+f"(d[0]), "+f"(d[1]), "+f"(d[2]), "+f"(d[3]), "+f"(d[4]), "+f"(d[5]), "+f"(d[6]), "+f"(d[7]),
          "+f"(d[8]), "+f"(d[9]), "+f"(d[10]), "+f"(d[11]), "+f"(d[12]), "+f"(d[13]), "+f"(d[14]), "+f"(d[15]),
          "+f"(d[16]), "+f"(d[17]), "+f"(d[18]), "+f"(d[19]), "+f"(d[20]), "+f"(d[21]), "+f"(d[22]), "+f"(d[23]),
          "+f"(d[24]), "+f"(d[25]), "+f"(d[26]), "+f"(d[27]), "+f"(d[28]), "+f"(d[29]), "+f"(d[30]), "+f"(d[31]),
          "+f"(d[32]), "+f"(d[33]), "+f"(d[34]), "+f"(d[35]), "+f"(d[36]), "+f"(d[37]), "+f"(d[38]), "+f"(d[39])
        : "l"(da), "l"(db), "n"(SCALE_D));
}
__device__ __forceinline__ void node_gemm(float (&d)[40], uint32_t wa, uint32_t xa) {
    const uint64_t da = desc_sw128(wa), db = desc_sw128(xa);
    wgmma_n80<0>(d, da, db);
    wgmma_n80<1>(d, da + 128, db + 2);
    wgmma_n80<1>(d, da + 256, db + 4);
    wgmma_n80<1>(d, da + 384, db + 6);
}
template <int NREG>
__device__ __forceinline__ void reg_fence(float (&d)[NREG]) {
    #pragma unroll
    for (int i = 0; i < NREG; i++) asm volatile("" : "+f"(d[i]) :: "memory");
}

__device__ __forceinline__ uint32_t pack_bf16(float lo, float hi) {
    uint32_t d; asm("cvt.rn.bf16x2.f32 %0, %1, %2;" : "=r"(d) : "f"(hi), "f"(lo)); return d;
}
__device__ __forceinline__ uint32_t fma_bf2(uint32_t a, uint32_t b, uint32_t c) {
    uint32_t d; asm("fma.rn.bf16x2 %0, %1, %2, %3;" : "=r"(d) : "r"(a), "r"(b), "r"(c)); return d;
}
__device__ __forceinline__ uint32_t add_bf2(uint32_t a, uint32_t b) {
    uint32_t d; asm("add.rn.bf16x2 %0, %1, %2;" : "=r"(d) : "r"(a), "r"(b)); return d;
}
__device__ __forceinline__ float ex2f(float x) {
    float y; asm("ex2.approx.ftz.f32 %0, %1;" : "=f"(y) : "f"(x)); return y;
}
__device__ __forceinline__ uint32_t fma_relu_bf2(uint32_t a, uint32_t b, uint32_t c) {
    uint32_t d; asm("fma.rn.relu.bf16x2 %0, %1, %2, %3;" : "=r"(d) : "r"(a), "r"(b), "r"(c)); return d;
}
__device__ __forceinline__ uint32_t gate_pair(float y0, float y1, uint32_t neb, uint32_t niea) {
    const uint32_t na = fma_bf2(pack_bf16(ex2f(y0), ex2f(y1)), neb, niea);
    const uint32_t r0 = ~na;
    const uint32_t e  = fma_relu_bf2(na, r0, 0x40EF40EFu);
    return fma_bf2(r0, e, r0);
}

__device__ __forceinline__ uint4 ld_relaxed_128(const uint4* p) {
    unsigned __int128 t;
    asm volatile("ld.relaxed.gpu.global.b128 %0, [%1];" : "=q"(t) : "l"(p) : "memory");
    return make_uint4((uint32_t)t, (uint32_t)(t >> 32), (uint32_t)(t >> 64), (uint32_t)(t >> 96));
}
__device__ __forceinline__ void st_relaxed_128(uint4* p, uint4 v) {
    const unsigned __int128 t = (unsigned __int128)(((uint64_t)v.w << 32) | v.z) << 64 | (((uint64_t)v.y << 32) | v.x);
    asm volatile("st.relaxed.gpu.global.b128 [%0], %1;" :: "l"(p), "q"(t) : "memory");
}
__device__ __forceinline__ void sts32(uint32_t addr, uint32_t a) { asm volatile("st.shared.u32 [%0], %1;" :: "r"(addr), "r"(a) : "memory"); }
__device__ __forceinline__ uint32_t atoms_inc_if(uint32_t addr, bool p, uint32_t dflt) {
    uint32_t r = dflt;
    asm volatile("{\n\t.reg .pred p;\n\tsetp.ne.u32 p, %2, 0;\n\t@p atom.shared.add.u32 %0, [%1], 1;\n\t}"
                 : "+r"(r) : "r"(addr), "r"((uint32_t)p) : "memory");
    return r;
}
__device__ __forceinline__ uint32_t atoms_inc(uint32_t addr) {
    uint32_t r; asm volatile("atom.shared.add.u32 %0, [%1], 1;" : "=r"(r) : "r"(addr) : "memory"); return r;
}

__global__ void __launch_bounds__(NTHREADS, 1)
gatedgcn_kernel(const __nv_bfloat16* __restrict__ x, const __nv_bfloat16* __restrict__ e_attr,
                const int* __restrict__ src, const int* __restrict__ dst,
                const __nv_bfloat16* __restrict__ w_a, const __nv_bfloat16* __restrict__ w_b,
                const __nv_bfloat16* __restrict__ w_c, const __nv_bfloat16* __restrict__ w_u,
                const __nv_bfloat16* __restrict__ w_v, __nv_bfloat16* __restrict__ out) {
    extern __shared__ __align__(1024) unsigned char smem[];
    const uint32_t sb = (uint32_t)__cvta_generic_to_shared(smem);
    const int tid = threadIdx.x, lane = tid & 31;
    const int warp = uni(tid >> 5);
    const int cta = blockIdx.x;
    const int node0 = cta * NPB;
    const int g = lane >> 2, q = lane & 3;

    int* s_cnt  = (int*)(smem + SM_CNT);
    int* s_ncnt = (int*)(smem + SM_NCNT);
    volatile int* s_misc = (volatile int*)(smem + SM_MISC);

    auto load_weights = [&](int t, int nt) {
        #pragma unroll 1
        for (int i = t; i < 512; i += nt) {
            const uint32_t so = sb + SM_W + (i >> 3) * 128 + (((i ^ (i >> 3)) & 7) << 4);
            cp_async16(so + WS_B, w_b + i * 8);
            cp_async16(so + WS_V, w_v + i * 8);
            cp_async16(so + WS_A, w_a + i * 8);
            cp_async16(so + WS_U, w_u + i * 8);
        }
        if (t < 128) cp_async16(sb + SM_W + WS_C + (t >> 3) * 128 + (((t ^ (t >> 3)) & 7) << 4), w_c + t * 8);
    };

    auto store_rows = [&](const float (&d)[40], uint32_t base, int ld) {
        base += ((lane & 7) + ((lane >> 4) << 3)) * ld + ((warp & 3) * 16 + ((lane >> 3) & 1) * 8) * 2;
        #pragma unroll
        for (int w = 0; w < 10; w += 2)
            stsm_x4_t(base + w * 8 * ld,
                      pack_bf16(d[4 * w + 0], d[4 * w + 1]), pack_bf16(d[4 * w + 2], d[4 * w + 3]),
                      pack_bf16(d[4 * w + 4], d[4 * w + 5]), pack_bf16(d[4 * w + 6], d[4 * w + 7]));
    };
    auto neg_exp = [&](float (&d)[40], float scale, int slot) {
        float mx = 0.f;
        #pragma unroll
        for (int i = 0; i < 40; i++) { mx = fmaxf(mx, fabsf(d[i])); d[i] = -ex2f(d[i] * scale); }
        const uint32_t mb = __reduce_max_sync(0xffffffffu, __float_as_uint(mx));
        if (lane == 0) atomicMax((unsigned int*)&s_misc[slot], mb);
    };

    PROF(0);
    if (warp < NET / 32) {
        const int ebase = cta * CHUNK;
        const int nvec = (min(CHUNK, N_EDGES - ebase)) >> 2;
        const int sg = tid / UMAIN, su = tid - sg * UMAIN;
        const bool act_last = sg + (UPT - 1) * SPP < NB;
        int4 dv[4], sv[4];
        bool has[4];
        #pragma unroll
        for (int k = 0; k < 4; k++) {
            const int o = tid + (k & 1) * NET, v = (k >> 1) * WVEC + o;
            has[k] = o < WVEC && v < nvec;
            if (k == 2) {
                if (tid < 272 + 80 + 4 && tid != 272 + 80) s_cnt[tid] = 0;
                bar_sync(1, NET);
            }
            if (k >= 2) has[k] = has[k] && (dv[0].x | sv[0].x | (has[1] ? dv[1].x | sv[1].x : 0)) >= 0;
            if (has[k]) {
                dv[k] = ldg_stream((const int4*)(dst + ebase) + v);
                sv[k] = ldg_stream((const int4*)(src + ebase) + v);
            }
        }
        uint32_t tag = 0;
        #pragma unroll
        for (int w = 0; w < 2; w++) {
            if (w == 1) bar_sync(1, NET);
            #pragma unroll
            for (int k = 2 * w; k < 2 * w + 2; k++) {
                if (has[k]) {
                    const int v = tid + (k & 1) * NET;
                    const int dd[4] = {dv[k].x, dv[k].y, dv[k].z, dv[k].w};
                    const int ss[4] = {sv[k].x, sv[k].y, sv[k].z, sv[k].w};
                    uint32_t b[4], rank[4];
                    #pragma unroll
                    for (int j = 0; j < 4; j++) { b[j] = (uint32_t)dd[j] / NPB; rank[j] = (uint32_t)atomicAdd(&s_cnt[w * 136 + b[j]], 1); }
                    #pragma unroll
                    for (int j = 0; j < 4; j++) {
                        const uint32_t rec = (((uint32_t)(v * 4 + j) - b[j]) * NPB + (uint32_t)dd[j]) * N_NODES + (uint32_t)ss[j];
                        sts32(sb + SM_STAGE + (b[j] * SEG_LD + min(rank[j], (uint32_t)SEGCAP)) * 4, rec);
                    }
                }
            }
            if (w == 0) { bar_sync(8, NET + 32); tag = ((uint32_t)s_misc[0] + 1u) & 0xFFFFFFu; }
            else bar_sync(1, NET);
            PROF(1 + w);
            {
                const uint32_t a = sb + SM_STAGE + (sg * SEG_LD + 4 * su) * 4;
                uint4* gq = g_seg + (size_t)w * 2 * TAIL + ((size_t)sg * NB + cta) * UMAIN + su;
                uint32_t tmask = 0;
                uint4 pu[UPT];
                #pragma unroll
                for (int k = 0; k < UPT; k++) {
                    const bool on = k < UPT - 1 || act_last;
                    const int cnt = on ? s_cnt[w * 136 + sg + k * SPP] : 0, n = cnt - 4 * su;
                    const uint4 v = lds128(on ? a + k * SPP * SEG_LD * 4 : a);
                    pu[k].x = (n > 0 ? v.x : REC_NONE) | tag << 31;
                    pu[k].y = (n > 1 ? v.y : REC_NONE) | (tag >> 1) << 31;
                    pu[k].z = (n > 2 ? v.z : REC_NONE) | (tag >> 2) << 31;
                    pu[k].w = cnt > SEGCAP ? REC_OVF : (n > 3 ? v.w : REC_NONE) | (cnt > 4 * UMAIN + 3 * su ? 0x80000000u : 0u);
                    if (cnt > 4 * UMAIN + 3 * (su & ~1) && cnt <= SEGCAP) tmask |= 1u << k;
                }
                #pragma unroll
                for (int k = 0; k < UPT; k++)
                    if (k < UPT - 1 || act_last) st_relaxed_128(gq + (size_t)k * SPP * NB * UMAIN, pu[k]);
                while (tmask) {
                    const int k = __ffs(tmask) - 1;
                    tmask &= tmask - 1;
                    const uint32_t ta = a + (k * SPP * SEG_LD + 4 * UMAIN - su) * 4;
                    const int n = s_cnt[w * 136 + sg + k * SPP] - 4 * UMAIN - 3 * su;
                    st_relaxed_128(gq + (size_t)k * SPP * NB * UMAIN + TAIL,
                                   make_uint4(n > 0 ? lds32(ta) : REC_NONE, n > 1 ? lds32(ta + 4) : REC_NONE, n > 2 ? lds32(ta + 8) : REC_NONE, REC_NONE | tag));
                }
            }
        }
        PROF(3);
        const uint4* gp = g_seg + (size_t)cta * NB * UMAIN + tid;
        const uint32_t dcnt = sb + SM_DCNT + lane * 4, dump = sb + SM_DUMP + lane * 8 - CAPN * 8;
        const uint4 none = make_uint4(REC_NONE | tag << 31, REC_NONE | (tag >> 1) << 31, REC_NONE | (tag >> 2) << 31, REC_NONE | tag);
        uint4 rec[2 * UPT];
        auto fetch = [&](int w) {
            #pragma unroll
            for (int k = 0; k < UPT; k++) {
                rec[w * UPT + k] = none;
                if (k < UPT - 1 || act_last) rec[w * UPT + k] = ld_relaxed_128(gp + w * 2 * TAIL + k * SPP * UMAIN);
            }
        };
        fetch(0);
        bar_sync(3, NTHREADS);
        PROF(4);
        bool first = true;
        uint32_t todo = 3;
        #pragma unroll 1
        while (todo) {
            #pragma unroll
            for (int w = 0; w < 2; w++) {
                if (!(todo >> w & 1)) continue;
                bool more = false;
                for (int tries = 0;; tries++) {
                    bool ok = true;
                    #pragma unroll
                    for (int k = 0; k < UPT; k++) {
                        uint4& u = rec[w * UPT + k];
                        const bool stale = first ? (int)((u.x ^ none.x) | (u.y ^ none.y) | (u.z ^ none.z)) < 0 : u.w != none.w;
                        if (stale) { u = ld_relaxed_128(gp + w * 2 * TAIL + k * SPP * UMAIN); ok = false; }
                    }
                    if (__all_sync(0xffffffffu, ok)) break;
                    if (tries > 400000) {
                        s_misc[1] = 1;
                        #pragma unroll
                        for (int k = 0; k < UPT; k++) rec[w * UPT + k] = none;
                    }
                }
                uint32_t sv_[UPT][4], el[UPT][4], la[UPT][4], r[UPT][4];
                #pragma unroll
                for (int k = 0; k < UPT; k++) {
                    uint4& u = rec[w * UPT + k];
                    const uint32_t rw[4] = {u.x & 0x7FFFFFFFu, u.y & 0x7FFFFFFFu, u.z & 0x7FFFFFFFu, u.w & 0x7FFFFFFFu};
                    #pragma unroll
                    for (int j = 0; j < 4; j++) {
                        const uint32_t t = rw[j] / N_NODES;
                        el[k][j] = t / NPB;
                        const uint32_t dl = t - el[k][j] * NPB;
                        sv_[k][j] = (rw[j] - t * N_NODES) << 8;
                        const bool valid = rw[j] < REC_OVF;
                        la[k][j] = valid ? sb + SM_LIST + dl * LIST_LD : dump;
                        r[k][j] = atoms_inc(valid ? sb + SM_NCNT + dl * 4 : dcnt);
                    }
                    if (u.w == REC_OVF) s_misc[1] = 1;
                    const bool tl = (int)u.w < 0;
                    u = none;
                    if (tl) { u = ld_relaxed_128(gp + w * 2 * TAIL + k * SPP * UMAIN + TAIL); more = true; }
                }
                if (!__any_sync(0xffffffffu, more)) todo &= ~(1u << w);
                #pragma unroll
                for (int k = 0; k < UPT; k++)
                    #pragma unroll
                    for (int j = 0; j < 4; j++)
                        sts64(la[k][j] + min(r[k][j], (uint32_t)CAPN) * 8, sv_[k][j], ((sg + k * SPP) * CHUNK + w * (CHUNK / 2) + el[k][j]) * 32u);
                if (w == 0 && first) fetch(1);
            }
            first = false;
            gp += TAIL;
        }
        PROF(5);
    } else {
        const int wtid = tid - NET;
        uint32_t epoch = 0;
        if (wtid == 96) epoch = *(volatile unsigned int*)&g_epoch[cta * 8];
        {
            const uint32_t so = (wtid >> 3) * 128 + (((wtid ^ (wtid >> 3)) & 7) << 4);
            #pragma unroll
            for (int k = 0; k < 5; k++) {
                const int r = (wtid >> 3) + 16 * k;
                const bool ok = r < NPB && node0 + r < N_NODES;
                cp_async16_zfill(sb + SM_XOWN + so + k * 2048, x + (ok ? (size_t)node0 * 64 + wtid * 8 + k * 1024 : 0), ok ? 16 : 0);
            }
            #pragma unroll
            for (int k = 0; k < 4; k++) {
                cp_async16(sb + SM_W + WS_V + so + k * 2048, w_v + wtid * 8 + k * 1024);
                cp_async16(sb + SM_W + WS_B + so + k * 2048, w_b + wtid * 8 + k * 1024);
            }
            cp_commit();
            #pragma unroll
            for (int k = 0; k < 4; k++) {
                cp_async16(sb + SM_W + WS_A + so + k * 2048, w_a + wtid * 8 + k * 1024);
                cp_async16(sb + SM_W + WS_U + so + k * 2048, w_u + wtid * 8 + k * 1024);
            }
            cp_async16(sb + SM_W + WS_C + so, w_c + wtid * 8);
            cp_commit();
        }
        if (wtid >= 96) {
            if (lane == 0) { s_misc[0] = (int)epoch; g_epoch[cta * 8] = epoch + 1u; }
            __syncwarp();
            bar_arrive(8, NET + 32);
        }
        if (wtid < 8) sts128(sb + SM_LIST + NULLT + wtid * 16, NULL_W0, 0u, NULL_W0, 0u);
        if (wtid >= 8 && wtid < 12) s_misc[wtid - 4] = 0;
        if (wtid >= 32 && wtid < 96) s_misc[wtid - 24] = wtid < 64 ? 0 : CAPN;
        cp_wait<1>();
        fence_async();
        bar_sync(2, 128);
        {
            float db[40], dv[40];
            wgmma_fence();
            node_gemm(dv, sb + SM_W + WS_V, sb + SM_XOWN);
            wgmma_commit();
            node_gemm(db, sb + SM_W + WS_B, sb + SM_XOWN);
            wgmma_commit();
            wgmma_wait<1>();
            reg_fence(dv);
            store_rows(dv, sb + SM_T + 128, T_LD);
            float mv = 0.f;
            #pragma unroll
            for (int i = 0; i < 40; i++) mv = fmaxf(mv, fabsf(dv[i]));
            if (mv > 1e9f) s_misc[5] = 0x7F800000;
            wgmma_wait<0>();
            reg_fence(db);
            neg_exp(db, -L2E, 5);
            store_rows(db, sb + SM_T, T_LD);
        }
        bar_sync(2, 128);
        {
            uint4 v[10];
            #pragma unroll
            for (int k = 0; k < 10; k++)
                v[k] = lds128(sb + SM_T + ((wtid >> 4) + 8 * k) * T_LD + (wtid & 1) * 128 + ((wtid >> 1) & 7) * 16);
            #pragma unroll
            for (int k = 0; k < 10; k++) {
                const int r = (wtid >> 4) + 8 * k;
                if (node0 + r == N_NODES) v[k].x = v[k].y = v[k].z = v[k].w = (wtid & 1) ? 0u : 0xFF80FF80u;
                if (r < NPB && node0 + r <= N_NODES) g_tab[(size_t)node0 * 16 + wtid + k * 128] = v[k];
            }
        }
        cp_wait<0>();
        fence_async();
        bar_arrive(3, NTHREADS);
        bar_sync(2, 128);
        PROFG(12);
        const uint32_t ftag = (uint32_t)s_misc[0] + 1u;
        {
            float da[40], du[40];
            wgmma_fence();
            node_gemm(du, sb + SM_W + WS_U, sb + SM_XOWN);
            node_gemm(da, sb + SM_W + WS_A, sb + SM_XOWN);
            wgmma_commit();
            if (wtid == 96)
                asm volatile("st.release.gpu.global.u64 [%0], %1;"
                             :: "l"(&g_flag[cta]), "l"(((unsigned long long)ftag << 32) | (uint32_t)s_misc[5]) : "memory");
            __syncwarp();
            wgmma_wait<0>();
            reg_fence(du);
            reg_fence(da);
            store_rows(du, sb + SM_U, U_LD);
            neg_exp(da, L2E, 4);
            store_rows(da, sb + SM_IEA, U_LD);
        }
        if (wtid < 96) {
            #pragma unroll 2
            for (int i = wtid; i < 512; i += 96) {
                const int l = i >> 4, j = (i >> 1) & 7, h = i & 1;
                const int f = 32 * (j >> 2) + 8 * (l >> 3) + 2 * (j & 3) + ((l >> 2) & 1);
                const int r = 4 * (l & 3) + 2 * h;
                const unsigned char* wc = smem + SM_W + WS_C + (f & 7) * 2;
                const float c0 = __bfloat162float(*(const __nv_bfloat16*)(wc + r * 128 + (((f >> 3) ^ (r & 7)) << 4)));
                const float c1 = __bfloat162float(*(const __nv_bfloat16*)(wc + (r + 1) * 128 + (((f >> 3) ^ ((r + 1) & 7)) << 4)));
                ((uint32_t*)(smem + SM_WCF))[((i >> 2) & 3) * 128 + l * 4 + (i & 3)] = pack_bf16(c0 * -L2E, c1 * -L2E);
            }
            unsigned long long f0 = (unsigned long long)ftag << 32, f1 = f0;
            for (int tries = 0;; tries++) {
                if (wtid < NB / 2)
                    asm volatile("ld.acquire.gpu.global.v2.u64 {%0,%1}, [%2];" : "=l"(f0), "=l"(f1) : "l"(g_flag + 2 * wtid) : "memory");
                if (__all_sync(0xffffffffu, (uint32_t)(f0 >> 32) == ftag && (uint32_t)(f1 >> 32) == ftag)) break;
                if (tries > 100000) { f0 = 0x7F800000u; break; }
            }
            const uint32_t mx = __reduce_max_sync(0xffffffffu, max((uint32_t)f0, (uint32_t)f1));
            if (lane == 0) atomicMax((unsigned int*)&s_misc[6], mx);
            PROFG(11);
        }
    }
    __syncthreads();
    PROF(6);
    const bool bad_list = s_misc[1] != 0 ||
        __any_sync(0xffffffffu, max(max(s_ncnt[lane], s_ncnt[lane + 32]), s_ncnt[min(lane + 64, NPB - 1)]) > CAPN);

    auto reduce_rows = [&](float (&sum)[4], const uint32_t (&den)[8], const uint32_t (&num)[8]) {
        float s1[4] = {0.f, 0.f, 0.f, 0.f}, s2[4] = {0.f, 0.f, 0.f, 0.f};
        uint32_t ln;
        asm volatile("mov.u32 %0, %%laneid;" : "=r"(ln));
        #pragma unroll
        for (int j = 0; j < 4; j++) {
            const uint32_t sel = ((ln >> 2) & 3) == j ? 0x3F803F80u : 0u;
            mma_k16(s1, sel, 0u, 0u, sel, movm(den[j]), movm(num[j]), s1[0], s1[1], s1[2], s1[3]);
            mma_k16(s2, sel, 0u, 0u, sel, movm(den[j + 4]), movm(num[j + 4]), s2[0], s2[1], s2[2], s2[3]);
        }
        #pragma unroll
        for (int i = 0; i < 4; i++) sum[i] = ln < 16 ? s1[i] : s2[i];
    };
    auto write_node = [&](int node, const float (&sum)[4], int f0) {
        if (node0 + node < N_NODES) {
            const uint32_t iw = lds32(sb + SM_IEA + node * U_LD + f0 * 2);
            const uint32_t uw = lds32(sb + SM_U + node * U_LD + f0 * 2);
            const uint32_t xw = lds32(sb + SM_XOWN + node * 128 + (((f0 >> 3) ^ (node & 7)) << 4) + (f0 & 7) * 2);
            const float i0 = __uint_as_float(iw << 16), i1 = __uint_as_float(iw & 0xFFFF0000u);
            const float z0 = __uint_as_float(uw << 16) + __fdividef(sum[2] * i0, sum[0] * i0 - RSCALE * 1e-6f);
            const float z1 = __uint_as_float(uw & 0xFFFF0000u) + __fdividef(sum[3] * i1, sum[1] * i1 - RSCALE * 1e-6f);
            const float o0 = __uint_as_float(xw << 16) + fmaxf(z0, 0.f);
            const float o1 = __uint_as_float(xw & 0xFFFF0000u) + fmaxf(z1, 0.f);
            *(uint32_t*)(out + (size_t)(node0 + node) * 64 + f0) = pack_bf16(o0, o1);
        }
    };
    const char* eq = (const char*)e_attr + q * 8;
    const uint32_t la = sb + SM_LIST + g * 8;
    const bool fast = !bad_list && __int_as_float(s_misc[4]) + __int_as_float(s_misc[6]) <= RANGE_MAX;

    if (fast) {
        auto job_range = [&](int j, int& tb, int& te) {
            tb = NULLT; te = NULLT + 128;
            if (j >= NJOBS) return -1;
            const int n = j < NWHOLE ? j : NWHOLE + ((j - NWHOLE) >> 1);
            const int cnt = s_ncnt[n];
            const int nt = max(1, (cnt + 15) >> 4);
            if (cnt + lane < nt * 16) sts64(sb + SM_LIST + n * LIST_LD + (cnt + lane) * 8, NULL_W0, 0u);
            __syncwarp();
            const int mid = j < NWHOLE ? nt : (nt + 1) >> 1;
            const bool second = j >= NWHOLE && ((j - NWHOLE) & 1);
            if (!second) { tb = n * LIST_LD; te = tb + mid * 128; }
            else if (mid < nt) { tb = n * LIST_LD + mid * 128; te = n * LIST_LD + nt * 128; }
            return n;
        };
        const char* tabq = (const char*)g_tab + q * 32;
        asm volatile("" : "+l"(tabq));
        uint32_t wcf[16];
        #pragma unroll
        for (int i = 0; i < 4; i++) {
            const uint4 v = lds128(sb + SM_WCF + i * 512 + lane * 16);
            wcf[4 * i] = v.x; wcf[4 * i + 1] = v.y; wcf[4 * i + 2] = v.z; wcf[4 * i + 3] = v.w;
        }
        uint32_t eb[2][8], hq[2][8], ev[4];
        const char *p0, *p1;
        bool v0, v1;
        auto load_rec = [&](int tt) {
            const uint2 r0 = lds64(la + tt), r1 = lds64(la + tt + 64);
            p0 = tabq + r0.x; p1 = tabq + r1.x;
            v0 = r0.x != NULL_W0; v1 = r1.x != NULL_W0;
            ldg64_stream(ev[0], ev[2], eq + r0.y);
            ldg64_stream(ev[1], ev[3], eq + r1.y);
        };
        auto load_half = [&](int h) {
            ldg128(&eb[0][4 * h], p0 + 128 * h); ldg128(&eb[1][4 * h], p1 + 128 * h);
            ldg128(&hq[0][4 * h], p0 + 16 + 128 * h); ldg128(&hq[1][4 * h], p1 + 16 + 128 * h);
        };
        auto load_rows = [&]() { load_half(0); load_half(1); };
        const int yes = s_misc[1] == 0;
        int t, te;
        int node = job_range(warp, t, te);
        load_rec(t);
        load_rows();
        PROF(15);
        while (true) {
            int nnode = 0;
            uint32_t iea[8], den[8], num[8];
            {
                const uint4 w0 = lds128(sb + SM_IEA + node * U_LD + q * 16), w1 = lds128(sb + SM_IEA + node * U_LD + 64 + q * 16);
                iea[0] = w0.x; iea[1] = w0.y; iea[2] = w0.z; iea[3] = w0.w; iea[4] = w1.x; iea[5] = w1.y; iea[6] = w1.z; iea[7] = w1.w;
            }
            #pragma unroll
            for (int j = 0; j < 8; j++) { den[j] = 0u; num[j] = 0u; }
            bool last;
            do {
                const uint32_t a0 = v0 ? ev[0] : 0u, a1 = v1 ? ev[1] : 0u, a2 = v0 ? ev[2] : 0u, a3 = v1 ? ev[3] : 0u;
                t += 128;
                last = t == te;
                if (last) nnode = job_range(uni((int)atoms_inc_if(sb + SM_MISC + 12, lane == 0, 0u)) + NWARPS, t, te);
                load_rec(t);
                #pragma unroll
                for (int h = 0; h < 2; h++) {
                    if (h == 1) { int y = yes; asm volatile("" : "+r"(y) :: "memory"); if (!y) break; }
                    float d[16];
                    #pragma unroll
                    for (int j = 0; j < 4; j++)
                        mma_k16(&d[4 * j], a0, a1, a2, a3, wcf[8 * h + 2 * j], wcf[8 * h + 2 * j + 1], 0.f, 0.f, 0.f, 0.f);
                    #pragma unroll
                    for (int jj = 0; jj < 4; jj++) {
                        const int j = 4 * h + jj;
                        const uint32_t ra = gate_pair(d[4 * jj], d[4 * jj + 1], eb[0][j], iea[j]);
                        const uint32_t rb = gate_pair(d[4 * jj + 2], d[4 * jj + 3], eb[1][j], iea[j]);
                        den[j] = add_bf2(add_bf2(den[j], ra), rb);
                        num[j] = fma_bf2(rb, hq[1][j], fma_bf2(ra, hq[0][j], num[j]));
                    }
                    load_half(h);
                }
            } while (!last);
            const int f0 = 32 * (g >> 2) + 8 * q + 2 * (g & 3);
            float sum[4];
            reduce_rows(sum, den, num);
            bool mine = true;
            if (node >= NWHOLE) {
                const uint32_t st = sb + SM_STATE + (node - NWHOLE) * 4, pa = sb + SM_PART + (node - NWHOLE) * 512 + lane * 16;
                mine = uni((int)atoms_inc_if(st, lane == 0, 0u)) != 0;
                if (!mine) {
                    sts128(pa, __float_as_uint(sum[0]), __float_as_uint(sum[1]), __float_as_uint(sum[2]), __float_as_uint(sum[3]));
                    __threadfence_block();
                    __syncwarp();
                    if (lane == 0) atomicAdd((int*)(smem + (st - sb)), 2);
                } else {
                    while (*(volatile int*)(smem + (st - sb)) < 4) {}
                    __threadfence_block();
                    const uint4 o = lds128(pa);
                    sum[0] += __uint_as_float(o.x); sum[1] += __uint_as_float(o.y);
                    sum[2] += __uint_as_float(o.z); sum[3] += __uint_as_float(o.w);
                }
            }
            if (mine) write_node(node, sum, f0);
            if (nnode < 0) break;
            node = nnode;
        }
        PROFE();
    } else {
        float2* acc = g_acc + (size_t)cta * NPB * 64;
        __syncthreads();
        load_weights(tid, NTHREADS);
        cp_commit();
        for (int i = tid; i < NPB * 64; i += NTHREADS) acc[i] = make_float2(0.f, 0.f);
        cp_wait<0>();
        int scan_pos = bad_list ? 0 : N_EDGES;
        int pend = 0, pv = 0;
        int4 d4 = make_int4(0, 0, 0, 0);
        bool more = true;
        while (more) {
            if (bad_list) {
                __syncthreads();
                if (tid < 80) s_ncnt[tid] = 0;
                __syncthreads();
                while (true) {
                    const int dd[4] = {d4.x, d4.y, d4.z, d4.w};
                    #pragma unroll
                    for (int j = 0; j < 4; j++) {
                        if (pend >> j & 1) {
                            const int dl = dd[j] - node0;
                            const int r = atomicAdd(&s_ncnt[dl], 1);
                            if (r < CAPN) {
                                const int e = pv * 4 + j;
                                sts64(sb + SM_LIST + dl * LIST_LD + r * 8, (uint32_t)__ldg(src + e) << 8, (uint32_t)e * 32u);
                                pend &= ~(1 << j);
                            }
                        }
                    }
                    if (__syncthreads_or(pend)) break;
                    if (scan_pos >= N_EDGES) { more = false; break; }
                    pv = (scan_pos >> 2) + tid;
                    if (pv < N_EDGES / 4) {
                        d4 = __ldg((const int4*)dst + pv);
                        pend = ((uint32_t)(d4.x - node0) < NPB ? 1 : 0) | ((uint32_t)(d4.y - node0) < NPB ? 2 : 0)
                             | ((uint32_t)(d4.z - node0) < NPB ? 4 : 0) | ((uint32_t)(d4.w - node0) < NPB ? 8 : 0);
                    }
                    scan_pos += NTHREADS * 4;
                }
            } else {
                more = false;
                __syncthreads();
            }
            const uint32_t wrow = sb + SM_W + (lane & 15) * 128;
            #pragma unroll 1
            for (int job = warp; job < NPB * 4; job += NWARPS) {
                const int n = job >> 2, jp = job & 3;
                const int cnt = min(s_ncnt[n], CAPN);
                if (cnt == 0) continue;
                const uint32_t wa = wrow + (((2 * jp + (lane >> 4)) ^ (lane & 7)) << 4);
                float ca[8] = {0.f, 0.f, 0.f, 0.f, 0.f, 0.f, 0.f, 0.f};
                #pragma unroll
                for (int k = 0; k < 4; k++) {
                    const uint32_t a0 = lds32(sb + SM_XOWN + n * 128 + (((2 * k) ^ (n & 7)) << 4) + q * 4);
                    const uint32_t a2 = lds32(sb + SM_XOWN + n * 128 + (((2 * k + 1) ^ (n & 7)) << 4) + q * 4);
                    uint32_t b[4];
                    ldsm_x4_t(b, wa + WS_A + k * 2048);
                    mma_k16(&ca[0], a0, a0, a2, a2, b[0], b[1], ca[0], ca[1], ca[2], ca[3]);
                    mma_k16(&ca[4], a0, a0, a2, a2, b[2], b[3], ca[4], ca[5], ca[6], ca[7]);
                }
                float sd[4] = {0.f, 0.f, 0.f, 0.f}, sn[4] = {0.f, 0.f, 0.f, 0.f};
                #pragma unroll 1
                for (int i0 = 0; i0 < cnt; i0 += 16) {
                    const bool v0 = i0 + g < cnt, v1 = i0 + g + 8 < cnt;
                    const uint2 r0 = lds64(sb + SM_LIST + n * LIST_LD + (v0 ? i0 + g : 0) * 8);
                    const uint2 r1 = lds64(sb + SM_LIST + n * LIST_LD + (v1 ? i0 + g + 8 : 0) * 8);
                    const uint32_t* x0 = (const uint32_t*)((const char*)x + (r0.x >> 1)) + q;
                    const uint32_t* x1 = (const uint32_t*)((const char*)x + (r1.x >> 1)) + q;
                    const uint32_t* e0 = (const uint32_t*)((const char*)e_attr + r0.y) + q;
                    const uint32_t* e1 = (const uint32_t*)((const char*)e_attr + r1.y) + q;
                    float gg[8], hh[8] = {0.f, 0.f, 0.f, 0.f, 0.f, 0.f, 0.f, 0.f};
                    uint32_t b[4];
                    {
                        const uint32_t a0 = __ldg(e0), a1 = __ldg(e1), a2 = __ldg(e0 + 4), a3 = __ldg(e1 + 4);
                        ldsm_x4_t(b, wa + WS_C);
                        mma_k16(&gg[0], a0, a1, a2, a3, b[0], b[1], ca[0], ca[1], ca[2], ca[3]);
                        mma_k16(&gg[4], a0, a1, a2, a3, b[2], b[3], ca[4], ca[5], ca[6], ca[7]);
                    }
                    #pragma unroll
                    for (int k = 0; k < 4; k++) {
                        const uint32_t a0 = __ldg(x0 + 8 * k), a1 = __ldg(x1 + 8 * k), a2 = __ldg(x0 + 8 * k + 4), a3 = __ldg(x1 + 8 * k + 4);
                        ldsm_x4_t(b, wa + WS_B + k * 2048);
                        mma_k16(&gg[0], a0, a1, a2, a3, b[0], b[1], gg[0], gg[1], gg[2], gg[3]);
                        mma_k16(&gg[4], a0, a1, a2, a3, b[2], b[3], gg[4], gg[5], gg[6], gg[7]);
                        ldsm_x4_t(b, wa + WS_V + k * 2048);
                        mma_k16(&hh[0], a0, a1, a2, a3, b[0], b[1], hh[0], hh[1], hh[2], hh[3]);
                        mma_k16(&hh[4], a0, a1, a2, a3, b[2], b[3], hh[4], hh[5], hh[6], hh[7]);
                    }
                    #pragma unroll
                    for (int i = 0; i < 8; i++) {
                        const float eta = ((i & 2) ? v1 : v0) ? 1.0f / (1.0f + ex2f(gg[i] * -L2E)) : 0.f;
                        const int o = (i >> 2) * 2 + (i & 1);
                        sd[o] += eta;
                        sn[o] = fmaf(eta, hh[i], sn[o]);
                    }
                }
                #pragma unroll
                for (int i = 0; i < 4; i++) {
                    #pragma unroll
                    for (int o = 4; o < 32; o <<= 1) {
                        sd[i] += __shfl_xor_sync(0xffffffffu, sd[i], o);
                        sn[i] += __shfl_xor_sync(0xffffffffu, sn[i], o);
                    }
                }
                if (g == 0) {
                    #pragma unroll
                    for (int i = 0; i < 4; i++) {
                        float2* pa = acc + n * 64 + jp * 16 + (i >> 1) * 8 + 2 * q + (i & 1);
                        *pa = make_float2(pa->x + sd[i], pa->y + sn[i]);
                    }
                }
            }
        }
        __syncthreads();
        for (int i = tid; i < NPB * 64; i += NTHREADS) {
            const int n = i >> 6, f = i & 63;
            if (node0 + n < N_NODES) {
                const float2 a = acc[i];
                const float u = __bfloat162float(*(const __nv_bfloat16*)(smem + SM_U + n * U_LD + f * 2));
                const float xv = __bfloat162float(*(const __nv_bfloat16*)(smem + SM_XOWN + n * 128 + (((f >> 3) ^ (n & 7)) << 4) + (f & 7) * 2));
                out[(size_t)(node0 + n) * 64 + f] = __float2bfloat16(xv + fmaxf(u + a.y / (a.x + 1e-6f), 0.f));
            }
        }
    }
}

}

extern "C" void kernel_launch(void* const* d_in, const int* in_sizes, int n_in, void* d_out, int out_size) {
    (void)in_sizes; (void)n_in; (void)out_size;
    constexpr int SMEM = SM_TOTAL + 128;
    cudaFuncSetAttribute(gatedgcn_kernel, cudaFuncAttributeMaxDynamicSharedMemorySize, SMEM);
    gatedgcn_kernel<<<NB, NTHREADS, SMEM>>>(
        (const __nv_bfloat16*)d_in[0], (const __nv_bfloat16*)d_in[1], (const int*)d_in[2], (const int*)d_in[3],
        (const __nv_bfloat16*)d_in[4], (const __nv_bfloat16*)d_in[5], (const __nv_bfloat16*)d_in[6],
        (const __nv_bfloat16*)d_in[7], (const __nv_bfloat16*)d_in[8], (__nv_bfloat16*)d_out);
}
```

```cpp
#include <cuda_runtime.h>
#include <cuda_bf16.h>
#include <stdint.h>

namespace {

constexpr int N_NODES  = 10000;
constexpr int N_EDGES  = 640000;
constexpr int NB       = 132;
constexpr int NPB      = 76;
constexpr int CHUNK    = 4864;
constexpr int UMAIN    = 8;
constexpr int SEGCAP   = 7 * UMAIN;
constexpr int WVEC     = CHUNK / 8;
constexpr int SEG_LD   = SEGCAP + 4;
constexpr int CAPN     = 112;
constexpr int LIST_LD  = (CAPN + 1) * 8;
constexpr int NTHREADS = 512;
constexpr int NWARPS   = NTHREADS / 32;
constexpr int NET      = 384;
constexpr int NSPLIT   = 12;
constexpr int NWHOLE   = NPB - NSPLIT;
constexpr int NJOBS    = NWHOLE + 2 * NSPLIT;
constexpr int SPP      = NET / UMAIN;
constexpr int UPT      = (NB + SPP - 1) / SPP;
constexpr int TAIL     = NB * NB * UMAIN;
static_assert(UMAIN % 2 == 0 && NET % UMAIN == 0 && WVEC <= 2 * NET && SEG_LD % 4 == 0, "exchange geometry");
static_assert(NB * NPB > N_NODES && NB * CHUNK >= N_EDGES, "coverage");

constexpr int U_LD = 144;
constexpr int T_LD = 272;

constexpr int SM_XOWN  = 0;
constexpr int SM_LIST  = SM_XOWN + 80 * 128;
constexpr int SM_STAGE = SM_LIST;
constexpr int NULLT    = NPB * LIST_LD;
constexpr int SM_T     = SM_LIST + NULLT - 80 * T_LD;
constexpr int SM_W     = (SM_LIST + NULLT + 128 + 1023) / 1024 * 1024;
constexpr int W_BYTES  = (4 * 64 + 16) * 128;
constexpr int SM_IEA   = SM_W;
constexpr int SM_PART  = SM_W + 16384;
constexpr int SM_U     = SM_W + W_BYTES;
constexpr int SM_WCF   = SM_U + 80 * U_LD;
constexpr int SM_CNT   = SM_WCF + 2048;
constexpr int SM_NCNT  = SM_CNT + 2 * 136 * 4;
constexpr int SM_MISC  = SM_NCNT + 80 * 4;
constexpr int SM_STATE = SM_MISC + 8 * 4;
constexpr int SM_DCNT  = SM_STATE + 32 * 4;
constexpr int SM_DUMP  = SM_DCNT + 32 * 4;
constexpr int SM_TOTAL = SM_DUMP + 32 * 8;
static_assert(SM_STAGE + NB * SEG_LD * 4 <= SM_T && SM_T % 16 == 0, "staging fits");
static_assert(SM_W % 16 == 0 && NULLT % 16 == 0, "alignment");
constexpr uint32_t REC_NONE = 0x7F000000u, REC_OVF = 0x7E000000u;
static_assert((unsigned long long)CHUNK / 2 * NPB * N_NODES <= REC_OVF, "record fits 31 bits");
static_assert(80 * U_LD <= 16384 && NSPLIT <= 32, "aliases fit");
static_assert(SM_TOTAL <= 134144, "fits the 132 KB carve-out");

constexpr int WS_B = 0, WS_V = 8192, WS_A = 16384, WS_U = 24576, WS_C = 32768;

constexpr uint32_t NULL_W0 = (uint32_t)N_NODES * 256u;
constexpr float L2E = 1.4426950408889634f;
constexpr float RSCALE = 17.906f;
constexpr float USHIFT = 11.0f, RANGE_AB = 72.0f, RANGE_A = 50.0f;

__device__ __align__(128) unsigned int g_epoch[NB * 8];
__device__ __align__(128) unsigned long long g_flag[NB];
__device__ __align__(128) uint4 g_seg[(size_t)4 * NB * NB * UMAIN];
__device__ __align__(256) uint4 g_tab[(size_t)(N_NODES + 1) * 16];
__device__ float2 g_acc[(size_t)NB * NPB * 64];


__device__ __forceinline__ void cp_async16(uint32_t dst, const void* src) {
    asm volatile("cp.async.cg.shared.global [%0], [%1], 16;" :: "r"(dst), "l"(src) : "memory");
}
__device__ __forceinline__ void cp_async16_zfill(uint32_t dst, const void* src, int sz) {
    asm volatile("cp.async.cg.shared.global [%0], [%1], 16, %2;" :: "r"(dst), "l"(src), "r"(sz) : "memory");
}
__device__ __forceinline__ void cp_commit() { asm volatile("cp.async.commit_group;" ::: "memory"); }
template <int N> __device__ __forceinline__ void cp_wait() { asm volatile("cp.async.wait_group %0;" :: "n"(N) : "memory"); }
__device__ __forceinline__ void fence_async() { asm volatile("fence.proxy.async.shared::cta;" ::: "memory"); }
__device__ __forceinline__ void wgmma_fence() { asm volatile("wgmma.fence.sync.aligned;" ::: "memory"); }
__device__ __forceinline__ void wgmma_commit() { asm volatile("wgmma.commit_group.sync.aligned;" ::: "memory"); }
template <int N> __device__ __forceinline__ void wgmma_wait() { asm volatile("wgmma.wait_group.sync.aligned %0;" :: "n"(N) : "memory"); }
__device__ __forceinline__ void bar_sync(int id, int n) { asm volatile("bar.sync %0, %1;" :: "r"(id), "r"(n) : "memory"); }
__device__ __forceinline__ void bar_arrive(int id, int n) { asm volatile("bar.arrive %0, %1;" :: "r"(id), "r"(n) : "memory"); }
__device__ __forceinline__ int uni(int v) { return __shfl_sync(0xffffffffu, v, 0); }

__device__ __forceinline__ void ldsm_x4_t(uint32_t (&r)[4], uint32_t addr) {
    asm volatile("ldmatrix.sync.aligned.m8n8.x4.trans.shared.b16 {%0,%1,%2,%3}, [%4];"
                 : "=r"(r[0]), "=r"(r[1]), "=r"(r[2]), "=r"(r[3]) : "r"(addr) : "memory");
}
__device__ __forceinline__ void stsm_x4_t(uint32_t addr, uint32_t r0, uint32_t r1, uint32_t r2, uint32_t r3) {
    asm volatile("stmatrix.sync.aligned.m8n8.x4.trans.shared.b16 [%0], {%1,%2,%3,%4};"
                 :: "r"(addr), "r"(r0), "r"(r1), "r"(r2), "r"(r3) : "memory");
}
__device__ __forceinline__ uint32_t movm(uint32_t a) {
    uint32_t d; asm volatile("movmatrix.sync.aligned.m8n8.trans.b16 %0, %1;" : "=r"(d) : "r"(a)); return d;
}
__device__ __forceinline__ uint32_t lds32(uint32_t addr) {
    uint32_t v; asm volatile("ld.shared.u32 %0, [%1];" : "=r"(v) : "r"(addr) : "memory"); return v;
}
__device__ __forceinline__ uint2 lds64(uint32_t addr) {
    uint2 v; asm volatile("ld.shared.v2.u32 {%0,%1}, [%2];" : "=r"(v.x), "=r"(v.y) : "r"(addr) : "memory"); return v;
}
__device__ __forceinline__ uint4 lds128(uint32_t addr) {
    uint4 v; asm volatile("ld.shared.v4.u32 {%0,%1,%2,%3}, [%4];" : "=r"(v.x), "=r"(v.y), "=r"(v.z), "=r"(v.w) : "r"(addr) : "memory"); return v;
}
__device__ __forceinline__ void sts64(uint32_t addr, uint32_t a, uint32_t b) {
    asm volatile("st.shared.v2.u32 [%0], {%1,%2};" :: "r"(addr), "r"(a), "r"(b) : "memory");
}
__device__ __forceinline__ void sts128(uint32_t addr, uint32_t a, uint32_t b, uint32_t c, uint32_t d) {
    asm volatile("st.shared.v4.u32 [%0], {%1,%2,%3,%4};" :: "r"(addr), "r"(a), "r"(b), "r"(c), "r"(d) : "memory");
}
__device__ __forceinline__ void ldg128(uint32_t* r, const char* p) {
    asm volatile("ld.global.v4.u32 {%0,%1,%2,%3}, [%4];" : "=r"(r[0]), "=r"(r[1]), "=r"(r[2]), "=r"(r[3]) : "l"(p) : "memory");
}
__device__ __forceinline__ void ldg64_stream(uint32_t& a, uint32_t& b, const char* p) {
    asm volatile("ld.global.nc.L1::no_allocate.v2.u32 {%0,%1}, [%2];" : "=r"(a), "=r"(b) : "l"(p) : "memory");
}

__device__ __forceinline__ int4 ldg_stream(const int4* p) {
    int4 v;
    asm volatile("ld.volatile.global.v4.s32 {%0,%1,%2,%3}, [%4];" : "=r"(v.x), "=r"(v.y), "=r"(v.z), "=r"(v.w) : "l"(p) : "memory");
    return v;
}

__device__ __forceinline__ void mma_k16(float* d, uint32_t a0, uint32_t a1, uint32_t a2, uint32_t a3, uint32_t b0, uint32_t b1,
                                        float c0, float c1, float c2, float c3) {
    asm volatile("mma.sync.aligned.m16n8k16.row.col.f32.bf16.bf16.f32 {%0,%1,%2,%3}, {%4,%5,%6,%7}, {%8,%9}, {%10,%11,%12,%13};"
                 : "=f"(d[0]), "=f"(d[1]), "=f"(d[2]), "=f"(d[3])
                 : "r"(a0), "r"(a1), "r"(a2), "r"(a3), "r"(b0), "r"(b1), "f"(c0), "f"(c1), "f"(c2), "f"(c3));
}
__device__ __forceinline__ uint64_t desc_sw128(uint32_t saddr) {
    return (uint64_t)((saddr & 0x3FFFF) >> 4) | (1ull << 16) | (64ull << 32) | (1ull << 62);
}
template <int SCALE_D>
__device__ __forceinline__ void wgmma_n80(float (&d)[40], uint64_t da, uint64_t db) {
    asm volatile(
        "wgmma.mma_async.sync.aligned.m64n80k16.f32.bf16.bf16 "
        "{%0,%1,%2,%3,%4,%5,%6,%7,%8,%9,%10,%11,%12,%13,%14,%15,"
        "%16,%17,%18,%19,%20,%21,%22,%23,%24,%25,%26,%27,%28,%29,%30,%31,"
        "%32,%33,%34,%35,%36,%37,%38,%39}, "
        "%40, %41, %42, 1, 1, 1, 0;"
        : "+f"(d[0]), "+f"(d[1]), "+f"(d[2]), "+f"(d[3]), "+f"(d[4]), "+f"(d[5]), "+f"(d[6]), "+f"(d[7]),
          "+f"(d[8]), "+f"(d[9]), "+f"(d[10]), "+f"(d[11]), "+f"(d[12]), "+f"(d[13]), "+f"(d[14]), "+f"(d[15]),
          "+f"(d[16]), "+f"(d[17]), "+f"(d[18]), "+f"(d[19]), "+f"(d[20]), "+f"(d[21]), "+f"(d[22]), "+f"(d[23]),
          "+f"(d[24]), "+f"(d[25]), "+f"(d[26]), "+f"(d[27]), "+f"(d[28]), "+f"(d[29]), "+f"(d[30]), "+f"(d[31]),
          "+f"(d[32]), "+f"(d[33]), "+f"(d[34]), "+f"(d[35]), "+f"(d[36]), "+f"(d[37]), "+f"(d[38]), "+f"(d[39])
        : "l"(da), "l"(db), "n"(SCALE_D));
}
__device__ __forceinline__ void node_gemm(float (&d)[40], uint32_t wa, uint32_t xa) {
    const uint64_t da = desc_sw128(wa), db = desc_sw128(xa);
    wgmma_n80<0>(d, da, db);
    wgmma_n80<1>(d, da + 128, db + 2);
    wgmma_n80<1>(d, da + 256, db + 4);
    wgmma_n80<1>(d, da + 384, db + 6);
}
template <int NREG>
__device__ __forceinline__ void reg_fence(float (&d)[NREG]) {
    #pragma unroll
    for (int i = 0; i < NREG; i++) asm volatile("" : "+f"(d[i]) :: "memory");
}

__device__ __forceinline__ uint32_t pack_bf16(float lo, float hi) {
    uint32_t d; asm("cvt.rn.bf16x2.f32 %0, %1, %2;" : "=r"(d) : "f"(hi), "f"(lo)); return d;
}
__device__ __forceinline__ uint32_t fma_bf2(uint32_t a, uint32_t b, uint32_t c) {
    uint32_t d; asm("fma.rn.bf16x2 %0, %1, %2, %3;" : "=r"(d) : "r"(a), "r"(b), "r"(c)); return d;
}
__device__ __forceinline__ uint32_t add_bf2(uint32_t a, uint32_t b) {
    uint32_t d; asm("add.rn.bf16x2 %0, %1, %2;" : "=r"(d) : "r"(a), "r"(b)); return d;
}
__device__ __forceinline__ float ex2f(float x) {
    float y; asm("ex2.approx.ftz.f32 %0, %1;" : "=f"(y) : "f"(x)); return y;
}
__device__ __forceinline__ uint32_t fma_relu_bf2(uint32_t a, uint32_t b, uint32_t c) {
    uint32_t d; asm("fma.rn.relu.bf16x2 %0, %1, %2, %3;" : "=r"(d) : "r"(a), "r"(b), "r"(c)); return d;
}
__device__ __forceinline__ uint32_t gate_pair(float y0, float y1, uint32_t neb, uint32_t niea) {
    const uint32_t na = fma_bf2(pack_bf16(ex2f(y0), ex2f(y1)), neb, niea);
    const uint32_t r0 = ~na;
    const uint32_t e  = fma_relu_bf2(na, r0, 0x40EF40EFu);
    return fma_bf2(r0, e, r0);
}

__device__ __forceinline__ uint4 ld_relaxed_128(const uint4* p) {
    unsigned __int128 t;
    asm volatile("ld.relaxed.gpu.global.b128 %0, [%1];" : "=q"(t) : "l"(p) : "memory");
    return make_uint4((uint32_t)t, (uint32_t)(t >> 32), (uint32_t)(t >> 64), (uint32_t)(t >> 96));
}
__device__ __forceinline__ void st_relaxed_128(uint4* p, uint4 v) {
    const unsigned __int128 t = (unsigned __int128)(((uint64_t)v.w << 32) | v.z) << 64 | (((uint64_t)v.y << 32) | v.x);
    asm volatile("st.relaxed.gpu.global.b128 [%0], %1;" :: "l"(p), "q"(t) : "memory");
}
__device__ __forceinline__ void sts32(uint32_t addr, uint32_t a) { asm volatile("st.shared.u32 [%0], %1;" :: "r"(addr), "r"(a) : "memory"); }
__device__ __forceinline__ uint32_t atoms_inc_if(uint32_t addr, bool p, uint32_t dflt) {
    uint32_t r = dflt;
    asm volatile("{\n\t.reg .pred p;\n\tsetp.ne.u32 p, %2, 0;\n\t@p atom.shared.add.u32 %0, [%1], 1;\n\t}"
                 : "+r"(r) : "r"(addr), "r"((uint32_t)p) : "memory");
    return r;
}
__device__ __forceinline__ uint32_t atoms_inc(uint32_t addr) {
    uint32_t r; asm volatile("atom.shared.add.u32 %0, [%1], 1;" : "=r"(r) : "r"(addr) : "memory"); return r;
}

__global__ void __launch_bounds__(NTHREADS, 1)
gatedgcn_kernel(const __nv_bfloat16* __restrict__ x, const __nv_bfloat16* __restrict__ e_attr,
                const int* __restrict__ src, const int* __restrict__ dst,
                const __nv_bfloat16* __restrict__ w_a, const __nv_bfloat16* __restrict__ w_b,
                const __nv_bfloat16* __restrict__ w_c, const __nv_bfloat16* __restrict__ w_u,
                const __nv_bfloat16* __restrict__ w_v, __nv_bfloat16* __restrict__ out) {
    extern __shared__ __align__(1024) unsigned char smem[];
    const uint32_t sb = (uint32_t)__cvta_generic_to_shared(smem);
    const int tid = threadIdx.x, lane = tid & 31;
    const int warp = uni(tid >> 5);
    const int cta = blockIdx.x;
    const int node0 = cta * NPB;
    const int g = lane >> 2, q = lane & 3;

    int* s_cnt  = (int*)(smem + SM_CNT);
    int* s_ncnt = (int*)(smem + SM_NCNT);
    volatile int* s_misc = (volatile int*)(smem + SM_MISC);

    auto load_weights = [&](int t, int nt) {
        #pragma unroll 1
        for (int i = t; i < 512; i += nt) {
            const uint32_t so = sb + SM_W + (i >> 3) * 128 + (((i ^ (i >> 3)) & 7) << 4);
            cp_async16(so + WS_B, w_b + i * 8);
            cp_async16(so + WS_V, w_v + i * 8);
            cp_async16(so + WS_A, w_a + i * 8);
            cp_async16(so + WS_U, w_u + i * 8);
        }
        if (t < 128) cp_async16(sb + SM_W + WS_C + (t >> 3) * 128 + (((t ^ (t >> 3)) & 7) << 4), w_c + t * 8);
    };

    auto store_rows = [&](const float (&d)[40], uint32_t base, int ld) {
        base += ((lane & 7) + ((lane >> 4) << 3)) * ld + ((warp & 3) * 16 + ((lane >> 3) & 1) * 8) * 2;
        #pragma unroll
        for (int w = 0; w < 10; w += 2)
            stsm_x4_t(base + w * 8 * ld,
                      pack_bf16(d[4 * w + 0], d[4 * w + 1]), pack_bf16(d[4 * w + 2], d[4 * w + 3]),
                      pack_bf16(d[4 * w + 4], d[4 * w + 5]), pack_bf16(d[4 * w + 6], d[4 * w + 7]));
    };
    auto neg_exp = [&](float (&d)[40], float scale, float bias, int slot) {
        float mx = 0.f;
        #pragma unroll
        for (int i = 0; i < 40; i++) { mx = fmaxf(mx, fabsf(d[i])); d[i] = -ex2f(fmaf(d[i], scale, bias)); }
        const uint32_t mb = __reduce_max_sync(0xffffffffu, __float_as_uint(mx));
        if (lane == 0) atomicMax((unsigned int*)&s_misc[slot], mb);
    };
    if (warp < NET / 32) {
        const int ebase = cta * CHUNK;
        const int nvec = (min(CHUNK, N_EDGES - ebase)) >> 2;
        const int sg = tid / UMAIN, su = tid - sg * UMAIN;
        const bool act_last = sg + (UPT - 1) * SPP < NB;
        int4 dv[4], sv[4];
        bool has[4];
        #pragma unroll
        for (int k = 0; k < 4; k++) {
            const int o = tid + (k & 1) * NET, v = (k >> 1) * WVEC + o;
            has[k] = o < WVEC && v < nvec;
            if (k == 2) {
                if (tid < 272 + 80 + 4 && tid != 272 + 80) s_cnt[tid] = 0;
                bar_sync(1, NET);
            }
            if (k >= 2) has[k] = has[k] && (dv[0].x | sv[0].x | (has[1] ? dv[1].x | sv[1].x : 0)) >= 0;
            if (has[k]) {
                dv[k] = ldg_stream((const int4*)(dst + ebase) + v);
                sv[k] = ldg_stream((const int4*)(src + ebase) + v);
            }
        }
        uint32_t tag = 0;
        #pragma unroll
        for (int w = 0; w < 2; w++) {
            if (w == 1) bar_sync(1, NET);
            #pragma unroll
            for (int k = 2 * w; k < 2 * w + 2; k++) {
                if (has[k]) {
                    const int v = tid + (k & 1) * NET;
                    const int dd[4] = {dv[k].x, dv[k].y, dv[k].z, dv[k].w};
                    const int ss[4] = {sv[k].x, sv[k].y, sv[k].z, sv[k].w};
                    uint32_t b[4], rank[4];
                    #pragma unroll
                    for (int j = 0; j < 4; j++) { b[j] = (uint32_t)dd[j] / NPB; rank[j] = (uint32_t)atomicAdd(&s_cnt[w * 136 + b[j]], 1); }
                    #pragma unroll
                    for (int j = 0; j < 4; j++) {
                        const uint32_t rec = (((uint32_t)(v * 4 + j) - b[j]) * NPB + (uint32_t)dd[j]) * N_NODES + (uint32_t)ss[j];
                        sts32(sb + SM_STAGE + (b[j] * SEG_LD + min(rank[j], (uint32_t)SEGCAP)) * 4, rec);
                    }
                }
            }
            if (w == 0) { bar_sync(8, NET + 32); tag = ((uint32_t)s_misc[0] + 1u) & 0xFFFFFFu; }
            else bar_sync(1, NET);
            {
                const uint32_t a = sb + SM_STAGE + (sg * SEG_LD + 4 * su) * 4;
                uint4* gq = g_seg + (size_t)w * 2 * TAIL + ((size_t)sg * NB + cta) * UMAIN + su;
                uint32_t tmask = 0;
                uint4 pu[UPT];
                #pragma unroll
                for (int k = 0; k < UPT; k++) {
                    const bool on = k < UPT - 1 || act_last;
                    const int cnt = on ? s_cnt[w * 136 + sg + k * SPP] : 0, n = cnt - 4 * su;
                    const uint4 v = lds128(on ? a + k * SPP * SEG_LD * 4 : a);
                    pu[k].x = (n > 0 ? v.x : REC_NONE) | tag << 31;
                    pu[k].y = (n > 1 ? v.y : REC_NONE) | (tag >> 1) << 31;
                    pu[k].z = (n > 2 ? v.z : REC_NONE) | (tag >> 2) << 31;
                    pu[k].w = cnt > SEGCAP ? REC_OVF : (n > 3 ? v.w : REC_NONE) | (cnt > 4 * UMAIN + 3 * su ? 0x80000000u : 0u);
                    if (cnt > 4 * UMAIN + 3 * (su & ~1) && cnt <= SEGCAP) tmask |= 1u << k;
                }
                #pragma unroll
                for (int k = 0; k < UPT; k++)
                    if (k < UPT - 1 || act_last) st_relaxed_128(gq + (size_t)k * SPP * NB * UMAIN, pu[k]);
                while (tmask) {
                    const int k = __ffs(tmask) - 1;
                    tmask &= tmask - 1;
                    const uint32_t ta = a + (k * SPP * SEG_LD + 4 * UMAIN - su) * 4;
                    const int n = s_cnt[w * 136 + sg + k * SPP] - 4 * UMAIN - 3 * su;
                    st_relaxed_128(gq + (size_t)k * SPP * NB * UMAIN + TAIL,
                                   make_uint4(n > 0 ? lds32(ta) : REC_NONE, n > 1 ? lds32(ta + 4) : REC_NONE, n > 2 ? lds32(ta + 8) : REC_NONE, REC_NONE | tag));
                }
            }
        }
        const uint4* gp = g_seg + (size_t)cta * NB * UMAIN + tid;
        const uint32_t dcnt = sb + SM_DCNT + lane * 4, dump = sb + SM_DUMP + lane * 8 - CAPN * 8;
        const uint4 none = make_uint4(REC_NONE | tag << 31, REC_NONE | (tag >> 1) << 31, REC_NONE | (tag >> 2) << 31, REC_NONE | tag);
        uint4 rec[2 * UPT];
        auto fetch = [&](int w) {
            #pragma unroll
            for (int k = 0; k < UPT; k++) {
                rec[w * UPT + k] = none;
                if (k < UPT - 1 || act_last) rec[w * UPT + k] = ld_relaxed_128(gp + w * 2 * TAIL + k * SPP * UMAIN);
            }
        };
        fetch(0);
        bar_sync(3, NTHREADS);
        bool first = true;
        uint32_t todo = 3;
        #pragma unroll 1
        while (todo) {
            #pragma unroll
            for (int w = 0; w < 2; w++) {
                if (!(todo >> w & 1)) continue;
                bool more = false;
                for (int tries = 0;; tries++) {
                    bool ok = true;
                    #pragma unroll
                    for (int k = 0; k < UPT; k++) {
                        uint4& u = rec[w * UPT + k];
                        const bool stale = first ? (int)((u.x ^ none.x) | (u.y ^ none.y) | (u.z ^ none.z)) < 0 : u.w != none.w;
                        if (stale) { u = ld_relaxed_128(gp + w * 2 * TAIL + k * SPP * UMAIN); ok = false; }
                    }
                    if (__all_sync(0xffffffffu, ok)) break;
                    if (tries > 400000) {
                        s_misc[1] = 1;
                        #pragma unroll
                        for (int k = 0; k < UPT; k++) rec[w * UPT + k] = none;
                    }
                }
                uint32_t sv_[UPT][4], el[UPT][4], la[UPT][4], r[UPT][4];
                #pragma unroll
                for (int k = 0; k < UPT; k++) {
                    uint4& u = rec[w * UPT + k];
                    const uint32_t rw[4] = {u.x & 0x7FFFFFFFu, u.y & 0x7FFFFFFFu, u.z & 0x7FFFFFFFu, u.w & 0x7FFFFFFFu};
                    #pragma unroll
                    for (int j = 0; j < 4; j++) {
                        const uint32_t t = rw[j] / N_NODES;
                        el[k][j] = t / NPB;
                        const uint32_t dl = t - el[k][j] * NPB;
                        sv_[k][j] = (rw[j] - t * N_NODES) << 8;
                        const bool valid = rw[j] < REC_OVF;
                        la[k][j] = valid ? sb + SM_LIST + dl * LIST_LD : dump;
                        r[k][j] = atoms_inc(valid ? sb + SM_NCNT + dl * 4 : dcnt);
                    }
                    if (u.w == REC_OVF) s_misc[1] = 1;
                    const bool tl = (int)u.w < 0;
                    u = none;
                    if (tl) { u = ld_relaxed_128(gp + w * 2 * TAIL + k * SPP * UMAIN + TAIL); more = true; }
                }
                if (!__any_sync(0xffffffffu, more)) todo &= ~(1u << w);
                #pragma unroll
                for (int k = 0; k < UPT; k++)
                    #pragma unroll
                    for (int j = 0; j < 4; j++)
                        sts64(la[k][j] + min(r[k][j], (uint32_t)CAPN) * 8, sv_[k][j], ((sg + k * SPP) * CHUNK + w * (CHUNK / 2) + el[k][j]) * 32u);
                if (w == 0 && first) fetch(1);
            }
            first = false;
            gp += TAIL;
        }
    } else {
        const int wtid = tid - NET;
        uint32_t epoch = 0;
        if (wtid == 96) epoch = *(volatile unsigned int*)&g_epoch[cta * 8];
        {
            const uint32_t so = (wtid >> 3) * 128 + (((wtid ^ (wtid >> 3)) & 7) << 4);
            #pragma unroll
            for (int k = 0; k < 5; k++) {
                const int r = (wtid >> 3) + 16 * k;
                const bool ok = r < NPB && node0 + r < N_NODES;
                cp_async16_zfill(sb + SM_XOWN + so + k * 2048, x + (ok ? (size_t)node0 * 64 + wtid * 8 + k * 1024 : 0), ok ? 16 : 0);
            }
            #pragma unroll
            for (int k = 0; k < 4; k++) {
                cp_async16(sb + SM_W + WS_V + so + k * 2048, w_v + wtid * 8 + k * 1024);
                cp_async16(sb + SM_W + WS_B + so + k * 2048, w_b + wtid * 8 + k * 1024);
            }
            cp_commit();
            #pragma unroll
            for (int k = 0; k < 4; k++) {
                cp_async16(sb + SM_W + WS_A + so + k * 2048, w_a + wtid * 8 + k * 1024);
                cp_async16(sb + SM_W + WS_U + so + k * 2048, w_u + wtid * 8 + k * 1024);
            }
            cp_async16(sb + SM_W + WS_C + so, w_c + wtid * 8);
            cp_commit();
        }
        if (wtid >= 96) {
            if (lane == 0) { s_misc[0] = (int)epoch; g_epoch[cta * 8] = epoch + 1u; }
            __syncwarp();
            bar_arrive(8, NET + 32);
        }
        if (wtid < 8) sts128(sb + SM_LIST + NULLT + wtid * 16, NULL_W0, 0u, NULL_W0, 0u);
        if (wtid >= 8 && wtid < 12) s_misc[wtid - 4] = 0;
        if (wtid >= 32 && wtid < 96) s_misc[wtid - 24] = wtid < 64 ? 0 : CAPN;
        cp_wait<1>();
        fence_async();
        bar_sync(2, 128);
        {
            float db[40], dv[40];
            wgmma_fence();
            node_gemm(dv, sb + SM_W + WS_V, sb + SM_XOWN);
            wgmma_commit();
            node_gemm(db, sb + SM_W + WS_B, sb + SM_XOWN);
            wgmma_commit();
            wgmma_wait<1>();
            reg_fence(dv);
            store_rows(dv, sb + SM_T + 128, T_LD);
            float mv = 0.f;
            #pragma unroll
            for (int i = 0; i < 40; i++) mv = fmaxf(mv, fabsf(dv[i]));
            if (mv > 1e9f) s_misc[5] = 0x7F800000;
            wgmma_wait<0>();
            reg_fence(db);
            neg_exp(db, -L2E, 0.f, 5);
            store_rows(db, sb + SM_T, T_LD);
        }
        bar_sync(2, 128);
        {
            uint4 v[10];
            #pragma unroll
            for (int k = 0; k < 10; k++)
                v[k] = lds128(sb + SM_T + ((wtid >> 4) + 8 * k) * T_LD + (wtid & 1) * 128 + ((wtid >> 1) & 7) * 16);
            #pragma unroll
            for (int k = 0; k < 10; k++) {
                const int r = (wtid >> 4) + 8 * k;
                if (node0 + r == N_NODES) v[k].x = v[k].y = v[k].z = v[k].w = (wtid & 1) ? 0u : 0xFF80FF80u;
                if (r < NPB && node0 + r <= N_NODES) g_tab[(size_t)node0 * 16 + wtid + k * 128] = v[k];
            }
        }
        cp_wait<0>();
        fence_async();
        bar_arrive(3, NTHREADS);
        bar_sync(2, 128);
        const uint32_t ftag = (uint32_t)s_misc[0] + 1u;
        {
            float da[40], du[40];
            wgmma_fence();
            node_gemm(du, sb + SM_W + WS_U, sb + SM_XOWN);
            node_gemm(da, sb + SM_W + WS_A, sb + SM_XOWN);
            wgmma_commit();
            if (wtid == 96)
                asm volatile("st.release.gpu.global.u64 [%0], %1;"
                             :: "l"(&g_flag[cta]), "l"(((unsigned long long)ftag << 32) | (uint32_t)s_misc[5]) : "memory");
            __syncwarp();
            wgmma_wait<0>();
            reg_fence(du);
            reg_fence(da);
            store_rows(du, sb + SM_U, U_LD);
            neg_exp(da, L2E, -USHIFT, 4);
            store_rows(da, sb + SM_IEA, U_LD);
        }
        if (wtid < 96) {
            #pragma unroll 2
            for (int i = wtid; i < 512; i += 96) {
                const int l = i >> 4, j = (i >> 1) & 7, h = i & 1;
                const int f = 32 * (j >> 2) + 8 * (l >> 3) + 2 * (j & 3) + ((l >> 2) & 1);
                const int r = 4 * (l & 3) + 2 * h;
                const unsigned char* wc = smem + SM_W + WS_C + (f & 7) * 2;
                const float c0 = __bfloat162float(*(const __nv_bfloat16*)(wc + r * 128 + (((f >> 3) ^ (r & 7)) << 4)));
                const float c1 = __bfloat162float(*(const __nv_bfloat16*)(wc + (r + 1) * 128 + (((f >> 3) ^ ((r + 1) & 7)) << 4)));
                ((uint32_t*)(smem + SM_WCF))[((i >> 2) & 3) * 128 + l * 4 + (i & 3)] = pack_bf16(c0 * -L2E, c1 * -L2E);
            }
            unsigned long long f0 = (unsigned long long)ftag << 32, f1 = f0;
            for (int tries = 0;; tries++) {
                if (wtid < NB / 2)
                    asm volatile("ld.acquire.gpu.global.v2.u64 {%0,%1}, [%2];" : "=l"(f0), "=l"(f1) : "l"(g_flag + 2 * wtid) : "memory");
                if (__all_sync(0xffffffffu, (uint32_t)(f0 >> 32) == ftag && (uint32_t)(f1 >> 32) == ftag)) break;
                if (tries > 100000) { f0 = 0x7F800000u; break; }
            }
            const uint32_t mx = __reduce_max_sync(0xffffffffu, max((uint32_t)f0, (uint32_t)f1));
            if (lane == 0) atomicMax((unsigned int*)&s_misc[6], mx);
        }
    }
    __syncthreads();
    const bool bad_list = s_misc[1] != 0 ||
        __any_sync(0xffffffffu, max(max(s_ncnt[lane], s_ncnt[lane + 32]), s_ncnt[min(lane + 64, NPB - 1)]) > CAPN);

    auto reduce_rows = [&](float (&sum)[4], const uint32_t (&den)[8], const uint32_t (&num)[8]) {
        float s1[4] = {0.f, 0.f, 0.f, 0.f}, s2[4] = {0.f, 0.f, 0.f, 0.f};
        uint32_t ln;
        asm volatile("mov.u32 %0, %%laneid;" : "=r"(ln));
        #pragma unroll
        for (int j = 0; j < 4; j++) {
            const uint32_t sel = ((ln >> 2) & 3) == j ? 0x3F803F80u : 0u;
            mma_k16(s1, sel, 0u, 0u, sel, movm(den[j]), movm(num[j]), s1[0], s1[1], s1[2], s1[3]);
            mma_k16(s2, sel, 0u, 0u, sel, movm(den[j + 4]), movm(num[j + 4]), s2[0], s2[1], s2[2], s2[3]);
        }
        #pragma unroll
        for (int i = 0; i < 4; i++) sum[i] = ln < 16 ? s1[i] : s2[i];
    };
    auto write_node = [&](int node, const float (&sum)[4], int f0) {
        if (node0 + node < N_NODES) {
            const uint32_t iw = lds32(sb + SM_IEA + node * U_LD + f0 * 2);
            const uint32_t uw = lds32(sb + SM_U + node * U_LD + f0 * 2);
            const uint32_t xw = lds32(sb + SM_XOWN + node * 128 + (((f0 >> 3) ^ (node & 7)) << 4) + (f0 & 7) * 2);
            const float i0 = __uint_as_float(iw << 16), i1 = __uint_as_float(iw & 0xFFFF0000u);
            const float z0 = __uint_as_float(uw << 16) + __fdividef(sum[2] * i0, sum[0] * i0 - RSCALE * 1e-6f);
            const float z1 = __uint_as_float(uw & 0xFFFF0000u) + __fdividef(sum[3] * i1, sum[1] * i1 - RSCALE * 1e-6f);
            const float o0 = __uint_as_float(xw << 16) + fmaxf(z0, 0.f);
            const float o1 = __uint_as_float(xw & 0xFFFF0000u) + fmaxf(z1, 0.f);
            *(uint32_t*)(out + (size_t)(node0 + node) * 64 + f0) = pack_bf16(o0, o1);
        }
    };
    const char* eq = (const char*)e_attr + q * 8;
    const uint32_t la = sb + SM_LIST + g * 8;
    const bool fast = !bad_list && __int_as_float(s_misc[4]) <= RANGE_A && __int_as_float(s_misc[4]) + __int_as_float(s_misc[6]) <= RANGE_AB;

    if (fast) {
        auto job_range = [&](int j, int& tb, int& te) {
            tb = NULLT; te = NULLT + 128;
            if (j >= NJOBS) return -1;
            const int n = j < NWHOLE ? j : NWHOLE + ((j - NWHOLE) >> 1);
            const int cnt = s_ncnt[n];
            const int nt = max(1, (cnt + 15) >> 4);
            if (cnt + lane < nt * 16) sts64(sb + SM_LIST + n * LIST_LD + (cnt + lane) * 8, NULL_W0, 0u);
            __syncwarp();
            const int mid = j < NWHOLE ? nt : (nt + 1) >> 1;
            const bool second = j >= NWHOLE && ((j - NWHOLE) & 1);
            if (!second) { tb = n * LIST_LD; te = tb + mid * 128; }
            else if (mid < nt) { tb = n * LIST_LD + mid * 128; te = n * LIST_LD + nt * 128; }
            return n;
        };
        const char* tabq = (const char*)g_tab + q * 32;
        asm volatile("" : "+l"(tabq));
        uint32_t wcf[16];
        #pragma unroll
        for (int i = 0; i < 4; i++) {
            const uint4 v = lds128(sb + SM_WCF + i * 512 + lane * 16);
            wcf[4 * i] = v.x; wcf[4 * i + 1] = v.y; wcf[4 * i + 2] = v.z; wcf[4 * i + 3] = v.w;
        }
        uint32_t eb[2][8], hq[2][8], ev[4];
        const char *p0, *p1;
        bool v0, v1;
        auto load_rec = [&](int tt) {
            const uint2 r0 = lds64(la + tt), r1 = lds64(la + tt + 64);
            p0 = tabq + r0.x; p1 = tabq + r1.x;
            v0 = r0.x != NULL_W0; v1 = r1.x != NULL_W0;
            ldg64_stream(ev[0], ev[2], eq + r0.y);
            ldg64_stream(ev[1], ev[3], eq + r1.y);
        };
        auto load_half = [&](int h) {
            ldg128(&eb[0][4 * h], p0 + 128 * h); ldg128(&eb[1][4 * h], p1 + 128 * h);
            ldg128(&hq[0][4 * h], p0 + 16 + 128 * h); ldg128(&hq[1][4 * h], p1 + 16 + 128 * h);
        };
        auto load_rows = [&]() { load_half(0); load_half(1); };
        const int yes = s_misc[1] == 0;
        int t, te;
        int node = job_range(warp, t, te);
        load_rec(t);
        load_rows();
        while (true) {
            int nnode = 0;
            uint32_t iea[8], den[8], num[8];
            {
                const uint4 w0 = lds128(sb + SM_IEA + node * U_LD + q * 16), w1 = lds128(sb + SM_IEA + node * U_LD + 64 + q * 16);
                iea[0] = w0.x; iea[1] = w0.y; iea[2] = w0.z; iea[3] = w0.w; iea[4] = w1.x; iea[5] = w1.y; iea[6] = w1.z; iea[7] = w1.w;
            }
            #pragma unroll
            for (int j = 0; j < 8; j++) { den[j] = 0u; num[j] = 0u; }
            bool last;
            do {
                const uint32_t a0 = v0 ? ev[0] : 0u, a1 = v1 ? ev[1] : 0u, a2 = v0 ? ev[2] : 0u, a3 = v1 ? ev[3] : 0u;
                t += 128;
                last = t == te;
                if (last) nnode = job_range(uni((int)atoms_inc_if(sb + SM_MISC + 12, lane == 0, 0u)) + NWARPS, t, te);
                load_rec(t);
                #pragma unroll
                for (int h = 0; h < 2; h++) {
                    if (h == 1) { int y = yes; asm volatile("" : "+r"(y) :: "memory"); if (!y) break; }
                    float d[16];
                    #pragma unroll
                    for (int j = 0; j < 4; j++)
                        mma_k16(&d[4 * j], a0, a1, a2, a3, wcf[8 * h + 2 * j], wcf[8 * h + 2 * j + 1], -USHIFT, -USHIFT, -USHIFT, -USHIFT);
                    #pragma unroll
                    for (int jj = 0; jj < 4; jj++) {
                        const int j = 4 * h + jj;
                        const uint32_t ra = gate_pair(d[4 * jj], d[4 * jj + 1], eb[0][j], iea[j]);
                        const uint32_t rb = gate_pair(d[4 * jj + 2], d[4 * jj + 3], eb[1][j], iea[j]);
                        den[j] = add_bf2(add_bf2(den[j], ra), rb);
                        num[j] = fma_bf2(rb, hq[1][j], fma_bf2(ra, hq[0][j], num[j]));
                    }
                    load_half(h);
                }
            } while (!last);
            const int f0 = 32 * (g >> 2) + 8 * q + 2 * (g & 3);
            float sum[4];
            reduce_rows(sum, den, num);
            bool mine = true;
            if (node >= NWHOLE) {
                const uint32_t st = sb + SM_STATE + (node - NWHOLE) * 4, pa = sb + SM_PART + (node - NWHOLE) * 512 + lane * 16;
                mine = uni((int)atoms_inc_if(st, lane == 0, 0u)) != 0;
                if (!mine) {
                    sts128(pa, __float_as_uint(sum[0]), __float_as_uint(sum[1]), __float_as_uint(sum[2]), __float_as_uint(sum[3]));
                    __threadfence_block();
                    __syncwarp();
                    if (lane == 0) atomicAdd((int*)(smem + (st - sb)), 2);
                } else {
                    while (*(volatile int*)(smem + (st - sb)) < 4) {}
                    __threadfence_block();
                    const uint4 o = lds128(pa);
                    sum[0] += __uint_as_float(o.x); sum[1] += __uint_as_float(o.y);
                    sum[2] += __uint_as_float(o.z); sum[3] += __uint_as_float(o.w);
                }
            }
            if (mine) write_node(node, sum, f0);
            if (nnode < 0) break;
            node = nnode;
        }
    } else {
        float2* acc = g_acc + (size_t)cta * NPB * 64;
        __syncthreads();
        load_weights(tid, NTHREADS);
        cp_commit();
        for (int i = tid; i < NPB * 64; i += NTHREADS) acc[i] = make_float2(0.f, 0.f);
        cp_wait<0>();
        int scan_pos = bad_list ? 0 : N_EDGES;
        int pend = 0, pv = 0;
        int4 d4 = make_int4(0, 0, 0, 0);
        bool more = true;
        while (more) {
            if (bad_list) {
                __syncthreads();
                if (tid < 80) s_ncnt[tid] = 0;
                __syncthreads();
                while (true) {
                    const int dd[4] = {d4.x, d4.y, d4.z, d4.w};
                    #pragma unroll
                    for (int j = 0; j < 4; j++) {
                        if (pend >> j & 1) {
                            const int dl = dd[j] - node0;
                            const int r = atomicAdd(&s_ncnt[dl], 1);
                            if (r < CAPN) {
                                const int e = pv * 4 + j;
                                sts64(sb + SM_LIST + dl * LIST_LD + r * 8, (uint32_t)__ldg(src + e) << 8, (uint32_t)e * 32u);
                                pend &= ~(1 << j);
                            }
                        }
                    }
                    if (__syncthreads_or(pend)) break;
                    if (scan_pos >= N_EDGES) { more = false; break; }
                    pv = (scan_pos >> 2) + tid;
                    if (pv < N_EDGES / 4) {
                        d4 = __ldg((const int4*)dst + pv);
                        pend = ((uint32_t)(d4.x - node0) < NPB ? 1 : 0) | ((uint32_t)(d4.y - node0) < NPB ? 2 : 0)
                             | ((uint32_t)(d4.z - node0) < NPB ? 4 : 0) | ((uint32_t)(d4.w - node0) < NPB ? 8 : 0);
                    }
                    scan_pos += NTHREADS * 4;
                }
            } else {
                more = false;
                __syncthreads();
            }
            const uint32_t wrow = sb + SM_W + (lane & 15) * 128;
            #pragma unroll 1
            for (int job = warp; job < NPB * 4; job += NWARPS) {
                const int n = job >> 2, jp = job & 3;
                const int cnt = min(s_ncnt[n], CAPN);
                if (cnt == 0) continue;
                const uint32_t wa = wrow + (((2 * jp + (lane >> 4)) ^ (lane & 7)) << 4);
                float ca[8] = {0.f, 0.f, 0.f, 0.f, 0.f, 0.f, 0.f, 0.f};
                #pragma unroll
                for (int k = 0; k < 4; k++) {
                    const uint32_t a0 = lds32(sb + SM_XOWN + n * 128 + (((2 * k) ^ (n & 7)) << 4) + q * 4);
                    const uint32_t a2 = lds32(sb + SM_XOWN + n * 128 + (((2 * k + 1) ^ (n & 7)) << 4) + q * 4);
                    uint32_t b[4];
                    ldsm_x4_t(b, wa + WS_A + k * 2048);
                    mma_k16(&ca[0], a0, a0, a2, a2, b[0], b[1], ca[0], ca[1], ca[2], ca[3]);
                    mma_k16(&ca[4], a0, a0, a2, a2, b[2], b[3], ca[4], ca[5], ca[6], ca[7]);
                }
                float sd[4] = {0.f, 0.f, 0.f, 0.f}, sn[4] = {0.f, 0.f, 0.f, 0.f};
                #pragma unroll 1
                for (int i0 = 0; i0 < cnt; i0 += 16) {
                    const bool v0 = i0 + g < cnt, v1 = i0 + g + 8 < cnt;
                    const uint2 r0 = lds64(sb + SM_LIST + n * LIST_LD + (v0 ? i0 + g : 0) * 8);
                    const uint2 r1 = lds64(sb + SM_LIST + n * LIST_LD + (v1 ? i0 + g + 8 : 0) * 8);
                    const uint32_t* x0 = (const uint32_t*)((const char*)x + (r0.x >> 1)) + q;
                    const uint32_t* x1 = (const uint32_t*)((const char*)x + (r1.x >> 1)) + q;
                    const uint32_t* e0 = (const uint32_t*)((const char*)e_attr + r0.y) + q;
                    const uint32_t* e1 = (const uint32_t*)((const char*)e_attr + r1.y) + q;
                    float gg[8], hh[8] = {0.f, 0.f, 0.f, 0.f, 0.f, 0.f, 0.f, 0.f};
                    uint32_t b[4];
                    {
                        const uint32_t a0 = __ldg(e0), a1 = __ldg(e1), a2 = __ldg(e0 + 4), a3 = __ldg(e1 + 4);
                        ldsm_x4_t(b, wa + WS_C);
                        mma_k16(&gg[0], a0, a1, a2, a3, b[0], b[1], ca[0], ca[1], ca[2], ca[3]);
                        mma_k16(&gg[4], a0, a1, a2, a3, b[2], b[3], ca[4], ca[5], ca[6], ca[7]);
                    }
                    #pragma unroll
                    for (int k = 0; k < 4; k++) {
                        const uint32_t a0 = __ldg(x0 + 8 * k), a1 = __ldg(x1 + 8 * k), a2 = __ldg(x0 + 8 * k + 4), a3 = __ldg(x1 + 8 * k + 4);
                        ldsm_x4_t(b, wa + WS_B + k * 2048);
                        mma_k16(&gg[0], a0, a1, a2, a3, b[0], b[1], gg[0], gg[1], gg[2], gg[3]);
                        mma_k16(&gg[4], a0, a1, a2, a3, b[2], b[3], gg[4], gg[5], gg[6], gg[7]);
                        ldsm_x4_t(b, wa + WS_V + k * 2048);
                        mma_k16(&hh[0], a0, a1, a2, a3, b[0], b[1], hh[0], hh[1], hh[2], hh[3]);
                        mma_k16(&hh[4], a0, a1, a2, a3, b[2], b[3], hh[4], hh[5], hh[6], hh[7]);
                    }
                    #pragma unroll
                    for (int i = 0; i < 8; i++) {
                        const float eta = ((i & 2) ? v1 : v0) ? 1.0f / (1.0f + ex2f(gg[i] * -L2E)) : 0.f;
                        const int o = (i >> 2) * 2 + (i & 1);
                        sd[o] += eta;
                        sn[o] = fmaf(eta, hh[i], sn[o]);
                    }
                }
                #pragma unroll
                for (int i = 0; i < 4; i++) {
                    #pragma unroll
                    for (int o = 4; o < 32; o <<= 1) {
                        sd[i] += __shfl_xor_sync(0xffffffffu, sd[i], o);
                        sn[i] += __shfl_xor_sync(0xffffffffu, sn[i], o);
                    }
                }
                if (g == 0) {
                    #pragma unroll
                    for (int i = 0; i < 4; i++) {
                        float2* pa = acc + n * 64 + jp * 16 + (i >> 1) * 8 + 2 * q + (i & 1);
                        *pa = make_float2(pa->x + sd[i], pa->y + sn[i]);
                    }
                }
            }
        }
        __syncthreads();
        for (int i = tid; i < NPB * 64; i += NTHREADS) {
            const int n = i >> 6, f = i & 63;
            if (node0 + n < N_NODES) {
                const float2 a = acc[i];
                const float u = __bfloat162float(*(const __nv_bfloat16*)(smem + SM_U + n * U_LD + f * 2));
                const float xv = __bfloat162float(*(const __nv_bfloat16*)(smem + SM_XOWN + n * 128 + (((f >> 3) ^ (n & 7)) << 4) + (f & 7) * 2));
                out[(size_t)(node0 + n) * 64 + f] = __float2bfloat16(xv + fmaxf(u + a.y / (a.x + 1e-6f), 0.f));
            }
        }
    }
}

}

extern "C" void kernel_launch(void* const* d_in, const int* in_sizes, int n_in, void* d_out, int out_size) {
    (void)in_sizes; (void)n_in; (void)out_size;
    constexpr int SMEM = SM_TOTAL;
    cudaFuncSetAttribute(gatedgcn_kernel, cudaFuncAttributeMaxDynamicSharedMemorySize, SMEM);
    gatedgcn_kernel<<<NB, NTHREADS, SMEM>>>(
        (const __nv_bfloat16*)d_in[0], (const __nv_bfloat16*)d_in[1], (const int*)d_in[2], (const int*)d_in[3],
        (const __nv_bfloat16*)d_in[4], (const __nv_bfloat16*)d_in[5], (const __nv_bfloat16*)d_in[6],
        (const __nv_bfloat16*)d_in[7], (const __nv_bfloat16*)d_in[8], (__nv_bfloat16*)d_out);
}
```

```cpp
#include <cuda_runtime.h>
#include <cuda_bf16.h>
#include <stdint.h>

namespace {

constexpr int N_NODES  = 10000;
constexpr int N_EDGES  = 640000;
constexpr int NB       = 132;
constexpr int NPB      = 76;
constexpr int CHUNK    = 4864;
constexpr int UMAIN    = 8;
constexpr int SEGCAP   = 7 * UMAIN;
constexpr int WVEC     = CHUNK / 8;
constexpr int SEG_LD   = SEGCAP + 4;
constexpr int CAPN     = 112;
constexpr int LIST_LD  = (CAPN + 1) * 8;
constexpr int NTHREADS = 512;
constexpr int NWARPS   = NTHREADS / 32;
constexpr int NET      = 384;
constexpr int NSPLIT   = 8;
constexpr int NWHOLE   = NPB - NSPLIT;
constexpr int NJOBS    = NWHOLE + 2 * NSPLIT;
constexpr int SPP      = NET / UMAIN;
constexpr int UPT      = (NB + SPP - 1) / SPP;
constexpr int TAIL     = NB * NB * UMAIN;
static_assert(UMAIN % 2 == 0 && NET % UMAIN == 0 && WVEC <= 2 * NET && SEG_LD % 4 == 0, "exchange geometry");
static_assert(NB * NPB > N_NODES && NB * CHUNK >= N_EDGES, "coverage");

constexpr int U_LD = 144;
constexpr int T_LD = 272;

constexpr int SM_XOWN  = 0;
constexpr int SM_LIST  = SM_XOWN + 80 * 128;
constexpr int SM_STAGE = SM_LIST;
constexpr int NULLT    = NPB * LIST_LD;
constexpr int SM_T     = SM_LIST + NULLT - 80 * T_LD;
constexpr int SM_W     = (SM_LIST + NULLT + 128 + 1023) / 1024 * 1024;
constexpr int W_BYTES  = (4 * 64 + 16) * 128;
constexpr int SM_IEA   = SM_W;
constexpr int SM_PART  = SM_W + 16384;
constexpr int SM_U     = SM_W + W_BYTES;
constexpr int SM_WCF   = SM_U + 80 * U_LD;
constexpr int SM_CNT   = SM_WCF + 2048;
constexpr int SM_NCNT  = SM_CNT + 2 * 136 * 4;
constexpr int SM_MISC  = SM_NCNT + 80 * 4;
constexpr int SM_STATE = SM_MISC + 8 * 4;
constexpr int SM_DCNT  = SM_STATE + 32 * 4;
constexpr int SM_DUMP  = SM_DCNT + 32 * 4;
constexpr int SM_TOTAL = SM_DUMP + 32 * 8;
static_assert(SM_STAGE + NB * SEG_LD * 4 <= SM_T && SM_T % 16 == 0, "staging fits");
static_assert(SM_W % 16 == 0 && NULLT % 16 == 0, "alignment");
constexpr uint32_t REC_NONE = 0x7F000000u, REC_OVF = 0x7E000000u;
static_assert((unsigned long long)CHUNK / 2 * NPB * N_NODES <= REC_OVF, "record fits 31 bits");
static_assert(80 * U_LD <= 16384 && NSPLIT <= 32, "aliases fit");
static_assert(SM_TOTAL <= 134144, "fits the 132 KB carve-out");

constexpr int WS_B = 0, WS_V = 8192, WS_A = 16384, WS_U = 24576, WS_C = 32768;

constexpr uint32_t NULL_W0 = (uint32_t)N_NODES * 256u;
constexpr float L2E = 1.4426950408889634f;
constexpr float RSCALE = 17.906f;
constexpr float USHIFT = 11.0f, RANGE_AB = 72.0f, RANGE_A = 50.0f;

__device__ __align__(128) unsigned int g_epoch[NB * 8];
__device__ __align__(128) unsigned long long g_flag[NB];
__device__ __align__(128) uint4 g_seg[(size_t)4 * NB * NB * UMAIN];
__device__ __align__(256) uint4 g_tab[(size_t)(N_NODES + 1) * 16];
__device__ float2 g_acc[(size_t)NB * NPB * 64];


__device__ __forceinline__ void cp_async16(uint32_t dst, const void* src) {
    asm volatile("cp.async.cg.shared.global [%0], [%1], 16;" :: "r"(dst), "l"(src) : "memory");
}
__device__ __forceinline__ void cp_async16_zfill(uint32_t dst, const void* src, int sz) {
    asm volatile("cp.async.cg.shared.global [%0], [%1], 16, %2;" :: "r"(dst), "l"(src), "r"(sz) : "memory");
}
__device__ __forceinline__ void cp_commit() { asm volatile("cp.async.commit_group;" ::: "memory"); }
template <int N> __device__ __forceinline__ void cp_wait() { asm volatile("cp.async.wait_group %0;" :: "n"(N) : "memory"); }
__device__ __forceinline__ void fence_async() { asm volatile("fence.proxy.async.shared::cta;" ::: "memory"); }
__device__ __forceinline__ void wgmma_fence() { asm volatile("wgmma.fence.sync.aligned;" ::: "memory"); }
__device__ __forceinline__ void wgmma_commit() { asm volatile("wgmma.commit_group.sync.aligned;" ::: "memory"); }
template <int N> __device__ __forceinline__ void wgmma_wait() { asm volatile("wgmma.wait_group.sync.aligned %0;" :: "n"(N) : "memory"); }
__device__ __forceinline__ void bar_sync(int id, int n) { asm volatile("bar.sync %0, %1;" :: "r"(id), "r"(n) : "memory"); }
__device__ __forceinline__ void bar_arrive(int id, int n) { asm volatile("bar.arrive %0, %1;" :: "r"(id), "r"(n) : "memory"); }
__device__ __forceinline__ int uni(int v) { return __shfl_sync(0xffffffffu, v, 0); }

__device__ __forceinline__ void ldsm_x4_t(uint32_t (&r)[4], uint32_t addr) {
    asm volatile("ldmatrix.sync.aligned.m8n8.x4.trans.shared.b16 {%0,%1,%2,%3}, [%4];"
                 : "=r"(r[0]), "=r"(r[1]), "=r"(r[2]), "=r"(r[3]) : "r"(addr) : "memory");
}
__device__ __forceinline__ void stsm_x4_t(uint32_t addr, uint32_t r0, uint32_t r1, uint32_t r2, uint32_t r3) {
    asm volatile("stmatrix.sync.aligned.m8n8.x4.trans.shared.b16 [%0], {%1,%2,%3,%4};"
                 :: "r"(addr), "r"(r0), "r"(r1), "r"(r2), "r"(r3) : "memory");
}
__device__ __forceinline__ uint32_t movm(uint32_t a) {
    uint32_t d; asm volatile("movmatrix.sync.aligned.m8n8.trans.b16 %0, %1;" : "=r"(d) : "r"(a)); return d;
}
__device__ __forceinline__ uint32_t lds32(uint32_t addr) {
    uint32_t v; asm volatile("ld.shared.u32 %0, [%1];" : "=r"(v) : "r"(addr) : "memory"); return v;
}
__device__ __forceinline__ uint2 lds64(uint32_t addr) {
    uint2 v; asm volatile("ld.shared.v2.u32 {%0,%1}, [%2];" : "=r"(v.x), "=r"(v.y) : "r"(addr) : "memory"); return v;
}
__device__ __forceinline__ uint4 lds128(uint32_t addr) {
    uint4 v; asm volatile("ld.shared.v4.u32 {%0,%1,%2,%3}, [%4];" : "=r"(v.x), "=r"(v.y), "=r"(v.z), "=r"(v.w) : "r"(addr) : "memory"); return v;
}
__device__ __forceinline__ void sts64(uint32_t addr, uint32_t a, uint32_t b) {
    asm volatile("st.shared.v2.u32 [%0], {%1,%2};" :: "r"(addr), "r"(a), "r"(b) : "memory");
}
__device__ __forceinline__ void sts128(uint32_t addr, uint32_t a, uint32_t b, uint32_t c, uint32_t d) {
    asm volatile("st.shared.v4.u32 [%0], {%1,%2,%3,%4};" :: "r"(addr), "r"(a), "r"(b), "r"(c), "r"(d) : "memory");
}
__device__ __forceinline__ void ldg128(uint32_t* r, const char* p) {
    asm volatile("ld.global.v4.u32 {%0,%1,%2,%3}, [%4];" : "=r"(r[0]), "=r"(r[1]), "=r"(r[2]), "=r"(r[3]) : "l"(p) : "memory");
}
__device__ __forceinline__ void ldg64_stream(uint32_t& a, uint32_t& b, const char* p) {
    asm volatile("ld.global.nc.L1::no_allocate.v2.u32 {%0,%1}, [%2];" : "=r"(a), "=r"(b) : "l"(p) : "memory");
}

__device__ __forceinline__ int4 ldg_stream(const int4* p) {
    int4 v;
    asm volatile("ld.volatile.global.v4.s32 {%0,%1,%2,%3}, [%4];" : "=r"(v.x), "=r"(v.y), "=r"(v.z), "=r"(v.w) : "l"(p) : "memory");
    return v;
}

__device__ __forceinline__ void mma_k16(float* d, uint32_t a0, uint32_t a1, uint32_t a2, uint32_t a3, uint32_t b0, uint32_t b1,
                                        float c0, float c1, float c2, float c3) {
    asm volatile("mma.sync.aligned.m16n8k16.row.col.f32.bf16.bf16.f32 {%0,%1,%2,%3}, {%4,%5,%6,%7}, {%8,%9}, {%10,%11,%12,%13};"
                 : "=f"(d[0]), "=f"(d[1]), "=f"(d[2]), "=f"(d[3])
                 : "r"(a0), "r"(a1), "r"(a2), "r"(a3), "r"(b0), "r"(b1), "f"(c0), "f"(c1), "f"(c2), "f"(c3));
}
__device__ __forceinline__ uint64_t desc_sw128(uint32_t saddr) {
    return (uint64_t)((saddr & 0x3FFFF) >> 4) | (1ull << 16) | (64ull << 32) | (1ull << 62);
}
template <int SCALE_D>
__device__ __forceinline__ void wgmma_n80(float (&d)[40], uint64_t da, uint64_t db) {
    asm volatile(
        "wgmma.mma_async.sync.aligned.m64n80k16.f32.bf16.bf16 "
        "{%0,%1,%2,%3,%4,%5,%6,%7,%8,%9,%10,%11,%12,%13,%14,%15,"
        "%16,%17,%18,%19,%20,%21,%22,%23,%24,%25,%26,%27,%28,%29,%30,%31,"
        "%32,%33,%34,%35,%36,%37,%38,%39}, "
        "%40, %41, %42, 1, 1, 1, 0;"
        : "+f"(d[0]), "+f"(d[1]), "+f"(d[2]), "+f"(d[3]), "+f"(d[4]), "+f"(d[5]), "+f"(d[6]), "+f"(d[7]),
          "+f"(d[8]), "+f"(d[9]), "+f"(d[10]), "+f"(d[11]), "+f"(d[12]), "+f"(d[13]), "+f"(d[14]), "+f"(d[15]),
          "+f"(d[16]), "+f"(d[17]), "+f"(d[18]), "+f"(d[19]), "+f"(d[20]), "+f"(d[21]), "+f"(d[22]), "+f"(d[23]),
          "+f"(d[24]), "+f"(d[25]), "+f"(d[26]), "+f"(d[27]), "+f"(d[28]), "+f"(d[29]), "+f"(d[30]), "+f"(d[31]),
          "+f"(d[32]), "+f"(d[33]), "+f"(d[34]), "+f"(d[35]), "+f"(d[36]), "+f"(d[37]), "+f"(d[38]), "+f"(d[39])
        : "l"(da), "l"(db), "n"(SCALE_D));
}
__device__ __forceinline__ void node_gemm(float (&d)[40], uint32_t wa, uint32_t xa) {
    const uint64_t da = desc_sw128(wa), db = desc_sw128(xa);
    wgmma_n80<0>(d, da, db);
    wgmma_n80<1>(d, da + 128, db + 2);
    wgmma_n80<1>(d, da + 256, db + 4);
    wgmma_n80<1>(d, da + 384, db + 6);
}
template <int NREG>
__device__ __forceinline__ void reg_fence(float (&d)[NREG]) {
    #pragma unroll
    for (int i = 0; i < NREG; i++) asm volatile("" : "+f"(d[i]) :: "memory");
}

__device__ __forceinline__ uint32_t pack_bf16(float lo, float hi) {
    uint32_t d; asm("cvt.rn.bf16x2.f32 %0, %1, %2;" : "=r"(d) : "f"(hi), "f"(lo)); return d;
}
__device__ __forceinline__ uint32_t fma_bf2(uint32_t a, uint32_t b, uint32_t c) {
    uint32_t d; asm("fma.rn.bf16x2 %0, %1, %2, %3;" : "=r"(d) : "r"(a), "r"(b), "r"(c)); return d;
}
__device__ __forceinline__ uint32_t add_bf2(uint32_t a, uint32_t b) {
    uint32_t d; asm("add.rn.bf16x2 %0, %1, %2;" : "=r"(d) : "r"(a), "r"(b)); return d;
}
__device__ __forceinline__ float ex2f(float x) {
    float y; asm("ex2.approx.ftz.f32 %0, %1;" : "=f"(y) : "f"(x)); return y;
}
__device__ __forceinline__ float rcpf(float x) {
    float y; asm("rcp.approx.ftz.f32 %0, %1;" : "=f"(y) : "f"(x)); return y;
}
__device__ __forceinline__ uint32_t fma_relu_bf2(uint32_t a, uint32_t b, uint32_t c) {
    uint32_t d; asm("fma.rn.relu.bf16x2 %0, %1, %2, %3;" : "=r"(d) : "r"(a), "r"(b), "r"(c)); return d;
}
__device__ __forceinline__ uint32_t gate_pair(float y0, float y1, uint32_t neb, uint32_t niea) {
    const uint32_t na = fma_bf2(pack_bf16(ex2f(y0), ex2f(y1)), neb, niea);
    const uint32_t r0 = ~na;
    const uint32_t e  = fma_relu_bf2(na, r0, 0x40EF40EFu);
    return fma_bf2(r0, e, r0);
}

__device__ __forceinline__ uint4 ld_relaxed_128(const uint4* p) {
    unsigned __int128 t;
    asm volatile("ld.relaxed.gpu.global.b128 %0, [%1];" : "=q"(t) : "l"(p) : "memory");
    return make_uint4((uint32_t)t, (uint32_t)(t >> 32), (uint32_t)(t >> 64), (uint32_t)(t >> 96));
}
__device__ __forceinline__ void st_relaxed_128(uint4* p, uint4 v) {
    const unsigned __int128 t = (unsigned __int128)(((uint64_t)v.w << 32) | v.z) << 64 | (((uint64_t)v.y << 32) | v.x);
    asm volatile("st.relaxed.gpu.global.b128 [%0], %1;" :: "l"(p), "q"(t) : "memory");
}
__device__ __forceinline__ void sts32(uint32_t addr, uint32_t a) { asm volatile("st.shared.u32 [%0], %1;" :: "r"(addr), "r"(a) : "memory"); }
__device__ __forceinline__ uint32_t atoms_inc_if(uint32_t addr, bool p, uint32_t dflt) {
    uint32_t r = dflt;
    asm volatile("{\n\t.reg .pred p;\n\tsetp.ne.u32 p, %2, 0;\n\t@p atom.shared.inc.u32 %0, [%1], 0x7FFFFFFF;\n\t}"
                 : "+r"(r) : "r"(addr), "r"((uint32_t)p) : "memory");
    return r;
}
__device__ __forceinline__ uint32_t atoms_inc(uint32_t addr) {
    uint32_t r; asm volatile("atom.shared.add.u32 %0, [%1], 1;" : "=r"(r) : "r"(addr) : "memory"); return r;
}

__global__ void __launch_bounds__(NTHREADS, 1)
gatedgcn_kernel(const __nv_bfloat16* __restrict__ x, const __nv_bfloat16* __restrict__ e_attr,
                const int* __restrict__ src, const int* __restrict__ dst,
                const __nv_bfloat16* __restrict__ w_a, const __nv_bfloat16* __restrict__ w_b,
                const __nv_bfloat16* __restrict__ w_c, const __nv_bfloat16* __restrict__ w_u,
                const __nv_bfloat16* __restrict__ w_v, __nv_bfloat16* __restrict__ out) {
    extern __shared__ __align__(1024) unsigned char smem[];
    const uint32_t sb = (uint32_t)__cvta_generic_to_shared(smem);
    const int tid = threadIdx.x, lane = tid & 31;
    const int warp = uni(tid >> 5);
    const int cta = blockIdx.x;
    const int node0 = cta * NPB;
    const int g = lane >> 2, q = lane & 3;

    int* s_cnt  = (int*)(smem + SM_CNT);
    int* s_ncnt = (int*)(smem + SM_NCNT);
    volatile int* s_misc = (volatile int*)(smem + SM_MISC);

    auto load_weights = [&](int t, int nt) {
        #pragma unroll 1
        for (int i = t; i < 512; i += nt) {
            const uint32_t so = sb + SM_W + (i >> 3) * 128 + (((i ^ (i >> 3)) & 7) << 4);
            cp_async16(so + WS_B, w_b + i * 8);
            cp_async16(so + WS_V, w_v + i * 8);
            cp_async16(so + WS_A, w_a + i * 8);
            cp_async16(so + WS_U, w_u + i * 8);
        }
        if (t < 128) cp_async16(sb + SM_W + WS_C + (t >> 3) * 128 + (((t ^ (t >> 3)) & 7) << 4), w_c + t * 8);
    };

    auto store_rows = [&](const float (&d)[40], uint32_t base, int ld) {
        base += ((lane & 7) + ((lane >> 4) << 3)) * ld + ((warp & 3) * 16 + ((lane >> 3) & 1) * 8) * 2;
        #pragma unroll
        for (int w = 0; w < 10; w += 2)
            stsm_x4_t(base + w * 8 * ld,
                      pack_bf16(d[4 * w + 0], d[4 * w + 1]), pack_bf16(d[4 * w + 2], d[4 * w + 3]),
                      pack_bf16(d[4 * w + 4], d[4 * w + 5]), pack_bf16(d[4 * w + 6], d[4 * w + 7]));
    };
    auto neg_exp = [&](float (&d)[40], float scale, float bias, int slot) {
        float mx = 0.f;
        #pragma unroll
        for (int i = 0; i < 40; i++) { mx = fmaxf(mx, fabsf(d[i])); d[i] = -ex2f(fmaf(d[i], scale, bias)); }
        const uint32_t mb = __reduce_max_sync(0xffffffffu, __float_as_uint(mx));
        if (lane == 0) atomicMax((unsigned int*)&s_misc[slot], mb);
    };
    if (warp < NET / 32) {
        const int ebase = cta * CHUNK;
        const int nvec = (min(CHUNK, N_EDGES - ebase)) >> 2;
        const int sg = tid / UMAIN, su = tid - sg * UMAIN;
        const bool act_last = sg + (UPT - 1) * SPP < NB;
        int4 dv[4], sv[4];
        bool has[4];
        #pragma unroll
        for (int k = 0; k < 4; k++) {
            const int o = tid + (k & 1) * NET, v = (k >> 1) * WVEC + o;
            has[k] = o < WVEC && v < nvec;
            if (k == 2) {
                if (tid < 272 + 80 + 4 && tid != 272 + 80) s_cnt[tid] = 0;
                bar_sync(1, NET);
            }
            if (k >= 2) has[k] = has[k] && (dv[0].x | sv[0].x | (has[1] ? dv[1].x | sv[1].x : 0)) >= 0;
            if (has[k]) {
                dv[k] = ldg_stream((const int4*)(dst + ebase) + v);
                sv[k] = ldg_stream((const int4*)(src + ebase) + v);
            }
        }
        uint32_t tag = 0;
        #pragma unroll
        for (int w = 0; w < 2; w++) {
            if (w == 1) bar_sync(1, NET);
            #pragma unroll
            for (int k = 2 * w; k < 2 * w + 2; k++) {
                if (has[k]) {
                    const int v = tid + (k & 1) * NET;
                    const int dd[4] = {dv[k].x, dv[k].y, dv[k].z, dv[k].w};
                    const int ss[4] = {sv[k].x, sv[k].y, sv[k].z, sv[k].w};
                    uint32_t b[4], rank[4];
                    #pragma unroll
                    for (int j = 0; j < 4; j++) { b[j] = (uint32_t)dd[j] / NPB; rank[j] = (uint32_t)atomicAdd(&s_cnt[w * 136 + b[j]], 1); }
                    #pragma unroll
                    for (int j = 0; j < 4; j++) {
                        const uint32_t rec = (((uint32_t)(v * 4 + j) - b[j]) * NPB + (uint32_t)dd[j]) * N_NODES + (uint32_t)ss[j];
                        sts32(sb + SM_STAGE + (b[j] * SEG_LD + min(rank[j], (uint32_t)SEGCAP)) * 4, rec);
                    }
                }
            }
            if (w == 0) { bar_sync(8, NET + 32); tag = ((uint32_t)s_misc[0] + 1u) & 0xFFFFFFu; }
            else bar_sync(1, NET);
            {
                const uint32_t a = sb + SM_STAGE + (sg * SEG_LD + 4 * su) * 4;
                uint4* gq = g_seg + (size_t)w * 2 * TAIL + ((size_t)sg * NB + cta) * UMAIN + su;
                uint32_t tmask = 0;
                uint4 pu[UPT];
                #pragma unroll
                for (int k = 0; k < UPT; k++) {
                    const bool on = k < UPT - 1 || act_last;
                    const int cnt = on ? s_cnt[w * 136 + sg + k * SPP] : 0, n = cnt - 4 * su;
                    const uint4 v = lds128(on ? a + k * SPP * SEG_LD * 4 : a);
                    pu[k].x = (n > 0 ? v.x : REC_NONE) | tag << 31;
                    pu[k].y = (n > 1 ? v.y : REC_NONE) | (tag >> 1) << 31;
                    pu[k].z = (n > 2 ? v.z : REC_NONE) | (tag >> 2) << 31;
                    pu[k].w = cnt > SEGCAP ? REC_OVF : (n > 3 ? v.w : REC_NONE) | (cnt > 4 * UMAIN + 3 * su ? 0x80000000u : 0u);
                    if (cnt > 4 * UMAIN + 3 * (su & ~1) && cnt <= SEGCAP) tmask |= 1u << k;
                }
                #pragma unroll
                for (int k = 0; k < UPT; k++)
                    if (k < UPT - 1 || act_last) st_relaxed_128(gq + (size_t)k * SPP * NB * UMAIN, pu[k]);
                while (tmask) {
                    const int k = __ffs(tmask) - 1;
                    tmask &= tmask - 1;
                    const uint32_t ta = a + (k * SPP * SEG_LD + 4 * UMAIN - su) * 4;
                    const int n = s_cnt[w * 136 + sg + k * SPP] - 4 * UMAIN - 3 * su;
                    st_relaxed_128(gq + (size_t)k * SPP * NB * UMAIN + TAIL,
                                   make_uint4(n > 0 ? lds32(ta) : REC_NONE, n > 1 ? lds32(ta + 4) : REC_NONE, n > 2 ? lds32(ta + 8) : REC_NONE, REC_NONE | tag));
                }
            }
        }
        const uint4* gp = g_seg + (size_t)cta * NB * UMAIN + tid;
        const uint32_t dcnt = sb + SM_DCNT + lane * 4, dump = sb + SM_DUMP + lane * 8 - CAPN * 8;
        const uint4 none = make_uint4(REC_NONE | tag << 31, REC_NONE | (tag >> 1) << 31, REC_NONE | (tag >> 2) << 31, REC_NONE | tag);
        uint4 rec[2 * UPT];
        auto fetch = [&](int w) {
            #pragma unroll
            for (int k = 0; k < UPT; k++) {
                rec[w * UPT + k] = none;
                if (k < UPT - 1 || act_last) rec[w * UPT + k] = ld_relaxed_128(gp + w * 2 * TAIL + k * SPP * UMAIN);
            }
        };
        fetch(0);
        bar_sync(3, NTHREADS);
        bool first = true;
        uint32_t todo = 3;
        #pragma unroll 1
        while (todo) {
            #pragma unroll
            for (int w = 0; w < 2; w++) {
                if (!(todo >> w & 1)) continue;
                bool more = false;
                for (int tries = 0;; tries++) {
                    bool ok = true;
                    #pragma unroll
                    for (int k = 0; k < UPT; k++) {
                        uint4& u = rec[w * UPT + k];
                        const bool stale = first ? (int)((u.x ^ none.x) | (u.y ^ none.y) | (u.z ^ none.z)) < 0 : u.w != none.w;
                        if (stale) { u = ld_relaxed_128(gp + w * 2 * TAIL + k * SPP * UMAIN); ok = false; }
                    }
                    if (__all_sync(0xffffffffu, ok)) break;
                    if (tries > 400000) {
                        s_misc[1] = 1;
                        #pragma unroll
                        for (int k = 0; k < UPT; k++) rec[w * UPT + k] = none;
                    }
                }
                uint32_t sv_[UPT][4], el[UPT][4], la[UPT][4], r[UPT][4];
                #pragma unroll
                for (int k = 0; k < UPT; k++) {
                    uint4& u = rec[w * UPT + k];
                    const uint32_t rw[4] = {u.x & 0x7FFFFFFFu, u.y & 0x7FFFFFFFu, u.z & 0x7FFFFFFFu, u.w & 0x7FFFFFFFu};
                    #pragma unroll
                    for (int j = 0; j < 4; j++) {
                        const uint32_t t = rw[j] / N_NODES;
                        el[k][j] = t / NPB;
                        const uint32_t dl = t - el[k][j] * NPB;
                        sv_[k][j] = (rw[j] - t * N_NODES) << 8;
                        const bool valid = rw[j] < REC_OVF;
                        la[k][j] = valid ? sb + SM_LIST + dl * LIST_LD : dump;
                        r[k][j] = atoms_inc(valid ? sb + SM_NCNT + dl * 4 : dcnt);
                    }
                    if (u.w == REC_OVF) s_misc[1] = 1;
                    const bool tl = (int)u.w < 0;
                    u = none;
                    if (tl) { u = ld_relaxed_128(gp + w * 2 * TAIL + k * SPP * UMAIN + TAIL); more = true; }
                }
                if (!__any_sync(0xffffffffu, more)) todo &= ~(1u << w);
                #pragma unroll
                for (int k = 0; k < UPT; k++)
                    #pragma unroll
                    for (int j = 0; j < 4; j++)
                        sts64(la[k][j] + min(r[k][j], (uint32_t)CAPN) * 8, sv_[k][j], ((sg + k * SPP) * CHUNK + w * (CHUNK / 2) + el[k][j]) * 32u);
                if (w == 0 && first) fetch(1);
            }
            first = false;
            gp += TAIL;
        }
    } else {
        const int wtid = tid - NET;
        uint32_t epoch = 0;
        if (wtid == 96) epoch = *(volatile unsigned int*)&g_epoch[cta * 8];
        {
            const uint32_t so = (wtid >> 3) * 128 + (((wtid ^ (wtid >> 3)) & 7) << 4);
            #pragma unroll
            for (int k = 0; k < 5; k++) {
                const int r = (wtid >> 3) + 16 * k;
                const bool ok = r < NPB && node0 + r < N_NODES;
                cp_async16_zfill(sb + SM_XOWN + so + k * 2048, x + (ok ? (size_t)node0 * 64 + wtid * 8 + k * 1024 : 0), ok ? 16 : 0);
            }
            #pragma unroll
            for (int k = 0; k < 4; k++) {
                cp_async16(sb + SM_W + WS_V + so + k * 2048, w_v + wtid * 8 + k * 1024);
                cp_async16(sb + SM_W + WS_B + so + k * 2048, w_b + wtid * 8 + k * 1024);
            }
            cp_commit();
            #pragma unroll
            for (int k = 0; k < 4; k++) {
                cp_async16(sb + SM_W + WS_A + so + k * 2048, w_a + wtid * 8 + k * 1024);
                cp_async16(sb + SM_W + WS_U + so + k * 2048, w_u + wtid * 8 + k * 1024);
            }
            cp_async16(sb + SM_W + WS_C + so, w_c + wtid * 8);
            cp_commit();
        }
        if (wtid >= 96) {
            if (lane == 0) { s_misc[0] = (int)epoch; g_epoch[cta * 8] = epoch + 1u; }
            __syncwarp();
            bar_arrive(8, NET + 32);
        }
        if (wtid < 8) sts128(sb + SM_LIST + NULLT + wtid * 16, NULL_W0, 0u, NULL_W0, 0u);
        if (wtid >= 8 && wtid < 12) s_misc[wtid - 4] = 0;
        if (wtid >= 32 && wtid < 96) s_misc[wtid - 24] = wtid < 64 ? 0 : CAPN;
        cp_wait<1>();
        fence_async();
        bar_sync(2, 128);
        {
            float db[40], dv[40];
            wgmma_fence();
            node_gemm(dv, sb + SM_W + WS_V, sb + SM_XOWN);
            wgmma_commit();
            node_gemm(db, sb + SM_W + WS_B, sb + SM_XOWN);
            wgmma_commit();
            wgmma_wait<1>();
            reg_fence(dv);
            store_rows(dv, sb + SM_T + 128, T_LD);
            float mv = 0.f;
            #pragma unroll
            for (int i = 0; i < 40; i++) mv = fmaxf(mv, fabsf(dv[i]));
            if (mv > 1e9f) s_misc[5] = 0x7F800000;
            wgmma_wait<0>();
            reg_fence(db);
            neg_exp(db, -L2E, 0.f, 5);
            store_rows(db, sb + SM_T, T_LD);
        }
        bar_sync(2, 128);
        {
            uint4 v[10];
            #pragma unroll
            for (int k = 0; k < 10; k++)
                v[k] = lds128(sb + SM_T + ((wtid >> 4) + 8 * k) * T_LD + (wtid & 1) * 128 + ((wtid >> 1) & 7) * 16);
            #pragma unroll
            for (int k = 0; k < 10; k++) {
                const int r = (wtid >> 4) + 8 * k;
                if (node0 + r == N_NODES) v[k].x = v[k].y = v[k].z = v[k].w = (wtid & 1) ? 0u : 0xFF80FF80u;
                if (r < NPB && node0 + r <= N_NODES) g_tab[(size_t)node0 * 16 + wtid + k * 128] = v[k];
            }
        }
        cp_wait<0>();
        fence_async();
        bar_arrive(3, NTHREADS);
        bar_sync(2, 128);
        const uint32_t ftag = (uint32_t)s_misc[0] + 1u;
        {
            float da[40], du[40];
            wgmma_fence();
            node_gemm(du, sb + SM_W + WS_U, sb + SM_XOWN);
            node_gemm(da, sb + SM_W + WS_A, sb + SM_XOWN);
            wgmma_commit();
            if (wtid == 96)
                asm volatile("st.release.gpu.global.u64 [%0], %1;"
                             :: "l"(&g_flag[cta]), "l"(((unsigned long long)ftag << 32) | (uint32_t)s_misc[5]) : "memory");
            __syncwarp();
            wgmma_wait<0>();
            reg_fence(du);
            reg_fence(da);
            store_rows(du, sb + SM_U, U_LD);
            neg_exp(da, L2E, -USHIFT, 4);
            store_rows(da, sb + SM_IEA, U_LD);
        }
        if (wtid < 96) {
            #pragma unroll 2
            for (int i = wtid; i < 512; i += 96) {
                const int l = i >> 4, j = (i >> 1) & 7, h = i & 1;
                const int f = 32 * (j >> 2) + 8 * (l >> 3) + 2 * (j & 3) + ((l >> 2) & 1);
                const int r = 4 * (l & 3) + 2 * h;
                const unsigned char* wc = smem + SM_W + WS_C + (f & 7) * 2;
                const float c0 = __bfloat162float(*(const __nv_bfloat16*)(wc + r * 128 + (((f >> 3) ^ (r & 7)) << 4)));
                const float c1 = __bfloat162float(*(const __nv_bfloat16*)(wc + (r + 1) * 128 + (((f >> 3) ^ ((r + 1) & 7)) << 4)));
                ((uint32_t*)(smem + SM_WCF))[((i >> 2) & 3) * 128 + l * 4 + (i & 3)] = pack_bf16(c0 * -L2E, c1 * -L2E);
            }
            unsigned long long f0 = (unsigned long long)ftag << 32, f1 = f0;
            for (int tries = 0;; tries++) {
                if (wtid < NB / 2)
                    asm volatile("ld.acquire.gpu.global.v2.u64 {%0,%1}, [%2];" : "=l"(f0), "=l"(f1) : "l"(g_flag + 2 * wtid) : "memory");
                if (__all_sync(0xffffffffu, (uint32_t)(f0 >> 32) == ftag && (uint32_t)(f1 >> 32) == ftag)) break;
                if (tries > 100000) { f0 = 0x7F800000u; break; }
            }
            const uint32_t mx = __reduce_max_sync(0xffffffffu, max((uint32_t)f0, (uint32_t)f1));
            if (lane == 0) atomicMax((unsigned int*)&s_misc[6], mx);
        }
    }
    __syncthreads();
    const bool bad_list = s_misc[1] != 0 ||
        __any_sync(0xffffffffu, max(max(s_ncnt[lane], s_ncnt[lane + 32]), s_ncnt[min(lane + 64, NPB - 1)]) > CAPN);

    auto reduce_rows = [&](float (&sum)[4], const uint32_t (&den)[8], const uint32_t (&num)[8]) {
        float s1[4] = {0.f, 0.f, 0.f, 0.f}, s2[4] = {0.f, 0.f, 0.f, 0.f};
        uint32_t ln;
        asm volatile("mov.u32 %0, %%laneid;" : "=r"(ln));
        #pragma unroll
        for (int j = 0; j < 4; j++) {
            const uint32_t sel = ((ln >> 2) & 3) == j ? 0x3F803F80u : 0u;
            mma_k16(s1, sel, 0u, 0u, sel, movm(den[j]), movm(num[j]), s1[0], s1[1], s1[2], s1[3]);
            mma_k16(s2, sel, 0u, 0u, sel, movm(den[j + 4]), movm(num[j + 4]), s2[0], s2[1], s2[2], s2[3]);
        }
        #pragma unroll
        for (int i = 0; i < 4; i++) sum[i] = ln < 16 ? s1[i] : s2[i];
    };
    auto write_node = [&](int node, const float (&sum)[4], int f0) {
        if (node0 + node < N_NODES) {
            const uint32_t iw = lds32(sb + SM_IEA + node * U_LD + f0 * 2);
            const uint32_t uw = lds32(sb + SM_U + node * U_LD + f0 * 2);
            const uint32_t xw = lds32(sb + SM_XOWN + node * 128 + (((f0 >> 3) ^ (node & 7)) << 4) + (f0 & 7) * 2);
            const float i0 = __uint_as_float(iw << 16), i1 = __uint_as_float(iw & 0xFFFF0000u);
            const float z0 = __uint_as_float(uw << 16) + sum[2] * i0 * rcpf(fmaf(sum[0], i0, -RSCALE * 1e-6f));
            const float z1 = __uint_as_float(uw & 0xFFFF0000u) + sum[3] * i1 * rcpf(fmaf(sum[1], i1, -RSCALE * 1e-6f));
            const float o0 = __uint_as_float(xw << 16) + fmaxf(z0, 0.f);
            const float o1 = __uint_as_float(xw & 0xFFFF0000u) + fmaxf(z1, 0.f);
            *(uint32_t*)(out + (size_t)(node0 + node) * 64 + f0) = pack_bf16(o0, o1);
        }
    };
    const char* eq = (const char*)e_attr + q * 8;
    const uint32_t la = sb + SM_LIST + g * 8;
    const bool fast = !bad_list && __int_as_float(s_misc[4]) <= RANGE_A && __int_as_float(s_misc[4]) + __int_as_float(s_misc[6]) <= RANGE_AB;

    if (fast) {
        auto job_range = [&](int j, int& tb, int& te) {
            tb = NULLT; te = NULLT + 128;
            if (j >= NJOBS) return -1;
            const int n = j < NWHOLE ? j : NWHOLE + ((j - NWHOLE) >> 1);
            const int cnt = s_ncnt[n];
            const int nt = max(1, (cnt + 15) >> 4);
            if (cnt + lane < nt * 16) sts64(sb + SM_LIST + n * LIST_LD + (cnt + lane) * 8, NULL_W0, 0u);
            __syncwarp();
            const int mid = j < NWHOLE ? nt : (nt + 1) >> 1;
            const bool second = j >= NWHOLE && ((j - NWHOLE) & 1);
            if (!second) { tb = n * LIST_LD; te = tb + mid * 128; }
            else if (mid < nt) { tb = n * LIST_LD + mid * 128; te = n * LIST_LD + nt * 128; }
            return n;
        };
        const char* tabq = (const char*)g_tab + q * 32;
        asm volatile("" : "+l"(tabq));
        uint32_t wcf[16];
        #pragma unroll
        for (int i = 0; i < 4; i++) {
            const uint4 v = lds128(sb + SM_WCF + i * 512 + lane * 16);
            wcf[4 * i] = v.x; wcf[4 * i + 1] = v.y; wcf[4 * i + 2] = v.z; wcf[4 * i + 3] = v.w;
        }
        uint32_t eb[2][8], hq[2][8], ev[4];
        const char *p0, *p1;
        bool v0, v1;
        auto load_rec = [&](int tt) {
            const uint2 r0 = lds64(la + tt), r1 = lds64(la + tt + 64);
            p0 = tabq + r0.x; p1 = tabq + r1.x;
            v0 = r0.x != NULL_W0; v1 = r1.x != NULL_W0;
            ldg64_stream(ev[0], ev[2], eq + r0.y);
            ldg64_stream(ev[1], ev[3], eq + r1.y);
        };
        auto load_half = [&](int h) {
            ldg128(&eb[0][4 * h], p0 + 128 * h); ldg128(&eb[1][4 * h], p1 + 128 * h);
            ldg128(&hq[0][4 * h], p0 + 16 + 128 * h); ldg128(&hq[1][4 * h], p1 + 16 + 128 * h);
        };
        auto load_rows = [&]() { load_half(0); load_half(1); };
        const int yes = s_misc[1] == 0;
        int t, te;
        int node = job_range(warp, t, te);
        load_rec(t);
        load_rows();
        while (true) {
            int nnode = 0;
            uint32_t iea[8], den[8], num[8];
            {
                const uint4 w0 = lds128(sb + SM_IEA + node * U_LD + q * 16), w1 = lds128(sb + SM_IEA + node * U_LD + 64 + q * 16);
                iea[0] = w0.x; iea[1] = w0.y; iea[2] = w0.z; iea[3] = w0.w; iea[4] = w1.x; iea[5] = w1.y; iea[6] = w1.z; iea[7] = w1.w;
            }
            #pragma unroll
            for (int j = 0; j < 8; j++) { den[j] = 0u; num[j] = 0u; }
            bool last;
            do {
                const uint32_t a0 = v0 ? ev[0] : 0u, a1 = v1 ? ev[1] : 0u, a2 = v0 ? ev[2] : 0u, a3 = v1 ? ev[3] : 0u;
                const bool upper = __any_sync(0xffffffffu, v1);
                t += 128;
                last = t == te;
                if (last) nnode = job_range(uni((int)atoms_inc_if(sb + SM_MISC + 12, lane == 0, 0u)) + NWARPS, t, te);
                load_rec(t);
                if (upper) {
                    #pragma unroll
                    for (int h = 0; h < 2; h++) {
                        if (h == 1) { int y = yes; asm volatile("" : "+r"(y) :: "memory"); if (!y) break; }
                        float d[16];
                        #pragma unroll
                        for (int j = 0; j < 4; j++)
                            mma_k16(&d[4 * j], a0, a1, a2, a3, wcf[8 * h + 2 * j], wcf[8 * h + 2 * j + 1], -USHIFT, -USHIFT, -USHIFT, -USHIFT);
                        #pragma unroll
                        for (int jj = 0; jj < 4; jj++) {
                            const int j = 4 * h + jj;
                            const uint32_t ra = gate_pair(d[4 * jj], d[4 * jj + 1], eb[0][j], iea[j]);
                            const uint32_t rb = gate_pair(d[4 * jj + 2], d[4 * jj + 3], eb[1][j], iea[j]);
                            den[j] = add_bf2(add_bf2(den[j], ra), rb);
                            num[j] = fma_bf2(rb, hq[1][j], fma_bf2(ra, hq[0][j], num[j]));
                        }
                        load_half(h);
                    }
                } else {
                    #pragma unroll
                    for (int j = 0; j < 8; j++) {
                        float d[4];
                        mma_k16(d, a0, a1, a2, a3, wcf[2 * j], wcf[2 * j + 1], -USHIFT, -USHIFT, -USHIFT, -USHIFT);
                        const uint32_t ra = gate_pair(d[0], d[1], eb[0][j], iea[j]);
                        den[j] = add_bf2(den[j], ra);
                        num[j] = fma_bf2(ra, hq[0][j], num[j]);
                    }
                    load_rows();
                }
            } while (!last);
            const int f0 = 32 * (g >> 2) + 8 * q + 2 * (g & 3);
            float sum[4];
            reduce_rows(sum, den, num);
            bool mine = true;
            if (node >= NWHOLE) {
                const uint32_t st = sb + SM_STATE + (node - NWHOLE) * 4, pa = sb + SM_PART + (node - NWHOLE) * 512 + lane * 16;
                mine = uni((int)atoms_inc_if(st, lane == 0, 0u)) != 0;
                if (!mine) {
                    sts128(pa, __float_as_uint(sum[0]), __float_as_uint(sum[1]), __float_as_uint(sum[2]), __float_as_uint(sum[3]));
                    asm volatile("fence.acq_rel.cta;" ::: "memory");
                    __syncwarp();
                    if (lane == 0) atomicAdd((int*)(smem + (st - sb)), 2);
                } else {
                    while (*(volatile int*)(smem + (st - sb)) < 4) {}
                    asm volatile("fence.acq_rel.cta;" ::: "memory");
                    const uint4 o = lds128(pa);
                    sum[0] += __uint_as_float(o.x); sum[1] += __uint_as_float(o.y);
                    sum[2] += __uint_as_float(o.z); sum[3] += __uint_as_float(o.w);
                }
            }
            if (mine) write_node(node, sum, f0);
            if (nnode < 0) break;
            node = nnode;
        }
    } else {
        float2* acc = g_acc + (size_t)cta * NPB * 64;
        __syncthreads();
        load_weights(tid, NTHREADS);
        cp_commit();
        for (int i = tid; i < NPB * 64; i += NTHREADS) acc[i] = make_float2(0.f, 0.f);
        cp_wait<0>();
        int scan_pos = bad_list ? 0 : N_EDGES;
        int pend = 0, pv = 0;
        int4 d4 = make_int4(0, 0, 0, 0);
        bool more = true;
        while (more) {
            if (bad_list) {
                __syncthreads();
                if (tid < 80) s_ncnt[tid] = 0;
                __syncthreads();
                while (true) {
                    const int dd[4] = {d4.x, d4.y, d4.z, d4.w};
                    #pragma unroll
                    for (int j = 0; j < 4; j++) {
                        if (pend >> j & 1) {
                            const int dl = dd[j] - node0;
                            const int r = atomicAdd(&s_ncnt[dl], 1);
                            if (r < CAPN) {
                                const int e = pv * 4 + j;
                                sts64(sb + SM_LIST + dl * LIST_LD + r * 8, (uint32_t)__ldg(src + e) << 8, (uint32_t)e * 32u);
                                pend &= ~(1 << j);
                            }
                        }
                    }
                    if (__syncthreads_or(pend)) break;
                    if (scan_pos >= N_EDGES) { more = false; break; }
                    pv = (scan_pos >> 2) + tid;
                    if (pv < N_EDGES / 4) {
                        d4 = __ldg((const int4*)dst + pv);
                        pend = ((uint32_t)(d4.x - node0) < NPB ? 1 : 0) | ((uint32_t)(d4.y - node0) < NPB ? 2 : 0)
                             | ((uint32_t)(d4.z - node0) < NPB ? 4 : 0) | ((uint32_t)(d4.w - node0) < NPB ? 8 : 0);
                    }
                    scan_pos += NTHREADS * 4;
                }
            } else {
                more = false;
                __syncthreads();
            }
            const uint32_t wrow = sb + SM_W + (lane & 15) * 128;
            #pragma unroll 1
            for (int job = warp; job < NPB * 4; job += NWARPS) {
                const int n = job >> 2, jp = job & 3;
                const int cnt = min(s_ncnt[n], CAPN);
                if (cnt == 0) continue;
                const uint32_t wa = wrow + (((2 * jp + (lane >> 4)) ^ (lane & 7)) << 4);
                float ca[8] = {0.f, 0.f, 0.f, 0.f, 0.f, 0.f, 0.f, 0.f};
                #pragma unroll
                for (int k = 0; k < 4; k++) {
                    const uint32_t a0 = lds32(sb + SM_XOWN + n * 128 + (((2 * k) ^ (n & 7)) << 4) + q * 4);
                    const uint32_t a2 = lds32(sb + SM_XOWN + n * 128 + (((2 * k + 1) ^ (n & 7)) << 4) + q * 4);
                    uint32_t b[4];
                    ldsm_x4_t(b, wa + WS_A + k * 2048);
                    mma_k16(&ca[0], a0, a0, a2, a2, b[0], b[1], ca[0], ca[1], ca[2], ca[3]);
                    mma_k16(&ca[4], a0, a0, a2, a2, b[2], b[3], ca[4], ca[5], ca[6], ca[7]);
                }
                float sd[4] = {0.f, 0.f, 0.f, 0.f}, sn[4] = {0.f, 0.f, 0.f, 0.f};
                #pragma unroll 1
                for (int i0 = 0; i0 < cnt; i0 += 16) {
                    const bool v0 = i0 + g < cnt, v1 = i0 + g + 8 < cnt;
                    const uint2 r0 = lds64(sb + SM_LIST + n * LIST_LD + (v0 ? i0 + g : 0) * 8);
                    const uint2 r1 = lds64(sb + SM_LIST + n * LIST_LD + (v1 ? i0 + g + 8 : 0) * 8);
                    const uint32_t* x0 = (const uint32_t*)((const char*)x + (r0.x >> 1)) + q;
                    const uint32_t* x1 = (const uint32_t*)((const char*)x + (r1.x >> 1)) + q;
                    const uint32_t* e0 = (const uint32_t*)((const char*)e_attr + r0.y) + q;
                    const uint32_t* e1 = (const uint32_t*)((const char*)e_attr + r1.y) + q;
                    float gg[8], hh[8] = {0.f, 0.f, 0.f, 0.f, 0.f, 0.f, 0.f, 0.f};
                    uint32_t b[4];
                    {
                        const uint32_t a0 = __ldg(e0), a1 = __ldg(e1), a2 = __ldg(e0 + 4), a3 = __ldg(e1 + 4);
                        ldsm_x4_t(b, wa + WS_C);
                        mma_k16(&gg[0], a0, a1, a2, a3, b[0], b[1], ca[0], ca[1], ca[2], ca[3]);
                        mma_k16(&gg[4], a0, a1, a2, a3, b[2], b[3], ca[4], ca[5], ca[6], ca[7]);
                    }
                    #pragma unroll
                    for (int k = 0; k < 4; k++) {
                        const uint32_t a0 = __ldg(x0 + 8 * k), a1 = __ldg(x1 + 8 * k), a2 = __ldg(x0 + 8 * k + 4), a3 = __ldg(x1 + 8 * k + 4);
                        ldsm_x4_t(b, wa + WS_B + k * 2048);
                        mma_k16(&gg[0], a0, a1, a2, a3, b[0], b[1], gg[0], gg[1], gg[2], gg[3]);
                        mma_k16(&gg[4], a0, a1, a2, a3, b[2], b[3], gg[4], gg[5], gg[6], gg[7]);
                        ldsm_x4_t(b, wa + WS_V + k * 2048);
                        mma_k16(&hh[0], a0, a1, a2, a3, b[0], b[1], hh[0], hh[1], hh[2], hh[3]);
                        mma_k16(&hh[4], a0, a1, a2, a3, b[2], b[3], hh[4], hh[5], hh[6], hh[7]);
                    }
                    #pragma unroll
                    for (int i = 0; i < 8; i++) {
                        const float eta = ((i & 2) ? v1 : v0) ? 1.0f / (1.0f + ex2f(gg[i] * -L2E)) : 0.f;
                        const int o = (i >> 2) * 2 + (i & 1);
                        sd[o] += eta;
                        sn[o] = fmaf(eta, hh[i], sn[o]);
                    }
                }
                #pragma unroll
                for (int i = 0; i < 4; i++) {
                    #pragma unroll
                    for (int o = 4; o < 32; o <<= 1) {
                        sd[i] += __shfl_xor_sync(0xffffffffu, sd[i], o);
                        sn[i] += __shfl_xor_sync(0xffffffffu, sn[i], o);
                    }
                }
                if (g == 0) {
                    #pragma unroll
                    for (int i = 0; i < 4; i++) {
                        float2* pa = acc + n * 64 + jp * 16 + (i >> 1) * 8 + 2 * q + (i & 1);
                        *pa = make_float2(pa->x + sd[i], pa->y + sn[i]);
                    }
                }
            }
        }
        __syncthreads();
        for (int i = tid; i < NPB * 64; i += NTHREADS) {
            const int n = i >> 6, f = i & 63;
            if (node0 + n < N_NODES) {
                const float2 a = acc[i];
                const float u = __bfloat162float(*(const __nv_bfloat16*)(smem + SM_U + n * U_LD + f * 2));
                const float xv = __bfloat162float(*(const __nv_bfloat16*)(smem + SM_XOWN + n * 128 + (((f >> 3) ^ (n & 7)) << 4) + (f & 7) * 2));
                out[(size_t)(node0 + n) * 64 + f] = __float2bfloat16(xv + fmaxf(u + a.y / (a.x + 1e-6f), 0.f));
            }
        }
    }
}

}

extern "C" void kernel_launch(void* const* d_in, const int* in_sizes, int n_in, void* d_out, int out_size) {
    (void)in_sizes; (void)n_in; (void)out_size;
    constexpr int SMEM = SM_TOTAL;
    cudaFuncSetAttribute(gatedgcn_kernel, cudaFuncAttributeMaxDynamicSharedMemorySize, SMEM);
    gatedgcn_kernel<<<NB, NTHREADS, SMEM>>>(
        (const __nv_bfloat16*)d_in[0], (const __nv_bfloat16*)d_in[1], (const int*)d_in[2], (const int*)d_in[3],
        (const __nv_bfloat16*)d_in[4], (const __nv_bfloat16*)d_in[5], (const __nv_bfloat16*)d_in[6],
        (const __nv_bfloat16*)d_in[7], (const __nv_bfloat16*)d_in[8], (__nv_bfloat16*)d_out);
}
```

```cpp
#include <cuda_runtime.h>
#include <cuda_bf16.h>
#include <stdint.h>

namespace {

constexpr int N_NODES  = 10000;
constexpr int N_EDGES  = 640000;
constexpr int NB       = 132;
constexpr int NPB      = 76;
constexpr int CHUNK    = 4864;
constexpr int UMAIN    = 8;
constexpr int SEGCAP   = 7 * UMAIN;
constexpr int WVEC     = CHUNK / 8;
constexpr int SEG_LD   = SEGCAP + 4;
constexpr int CAPN     = 112;
constexpr int LIST_LD  = (CAPN + 1) * 8;
constexpr int NTHREADS = 512;
constexpr int NWARPS   = NTHREADS / 32;
constexpr int NET      = 384;
constexpr int NSPLIT   = 4;
constexpr int NWHOLE   = NPB - NSPLIT;
constexpr int NJOBS    = NWHOLE + 2 * NSPLIT;
constexpr int SPP      = NET / UMAIN;
constexpr int UPT      = (NB + SPP - 1) / SPP;
constexpr int TAIL     = NB * NB * UMAIN;
static_assert(UMAIN % 2 == 0 && NET % UMAIN == 0 && WVEC <= 2 * NET && SEG_LD % 4 == 0, "exchange geometry");
static_assert(NB * NPB > N_NODES && NB * CHUNK >= N_EDGES, "coverage");

constexpr int U_LD = 144;
constexpr int T_LD = 272;

constexpr int SM_XOWN  = 0;
constexpr int SM_LIST  = SM_XOWN + 80 * 128;
constexpr int SM_STAGE = SM_LIST;
constexpr int NULLT    = NPB * LIST_LD;
constexpr int SM_T     = SM_LIST + NULLT - 80 * T_LD;
constexpr int SM_W     = (SM_LIST + NULLT + 128 + 1023) / 1024 * 1024;
constexpr int W_BYTES  = (4 * 64 + 16) * 128;
constexpr int SM_IEA   = SM_W;
constexpr int SM_PART  = SM_W + 16384;
constexpr int SM_U     = SM_W + W_BYTES;
constexpr int SM_WCF   = SM_U + 80 * U_LD;
constexpr int SM_CNT   = SM_WCF + 2048;
constexpr int SM_NCNT  = SM_CNT + 2 * 136 * 4;
constexpr int SM_MISC  = SM_NCNT + 80 * 4;
constexpr int SM_STATE = SM_MISC + 8 * 4;
constexpr int SM_DCNT  = SM_STATE + 32 * 4;
constexpr int SM_DUMP  = SM_DCNT + 32 * 4;
constexpr int SM_TOTAL = SM_DUMP + 32 * 8;
static_assert(SM_STAGE + NB * SEG_LD * 4 <= SM_T && SM_T % 16 == 0, "staging fits");
static_assert(SM_W % 16 == 0 && NULLT % 16 == 0, "alignment");
constexpr uint32_t REC_NONE = 0x7F000000u, REC_OVF = 0x7E000000u;
static_assert((unsigned long long)CHUNK / 2 * NPB * N_NODES <= REC_OVF, "record fits 31 bits");
static_assert(80 * U_LD <= 16384 && NSPLIT <= 32, "aliases fit");
static_assert(SM_TOTAL <= 134144, "fits the 132 KB carve-out");

constexpr int WS_B = 0, WS_V = 8192, WS_A = 16384, WS_U = 24576, WS_C = 32768;

constexpr uint32_t NULL_W0 = (uint32_t)N_NODES * 256u;
constexpr float L2E = 1.4426950408889634f;
constexpr float RSCALE = 17.906f;
constexpr float USHIFT = 11.0f, RANGE_AB = 72.0f, RANGE_A = 50.0f;

__device__ __align__(128) unsigned int g_epoch[NB * 8];
__device__ __align__(128) unsigned long long g_flag[NB];
__device__ __align__(128) uint4 g_seg[(size_t)4 * NB * NB * UMAIN];
__device__ __align__(256) uint4 g_tab[(size_t)(N_NODES + 1) * 16];
__device__ float2 g_acc[(size_t)NB * NPB * 64];


__device__ __forceinline__ void cp_async16(uint32_t dst, const void* src) {
    asm volatile("cp.async.cg.shared.global [%0], [%1], 16;" :: "r"(dst), "l"(src) : "memory");
}
__device__ __forceinline__ void cp_async16_zfill(uint32_t dst, const void* src, int sz) {
    asm volatile("cp.async.cg.shared.global [%0], [%1], 16, %2;" :: "r"(dst), "l"(src), "r"(sz) : "memory");
}
__device__ __forceinline__ void cp_commit() { asm volatile("cp.async.commit_group;" ::: "memory"); }
template <int N> __device__ __forceinline__ void cp_wait() { asm volatile("cp.async.wait_group %0;" :: "n"(N) : "memory"); }
__device__ __forceinline__ void fence_async() { asm volatile("fence.proxy.async.shared::cta;" ::: "memory"); }
__device__ __forceinline__ void wgmma_fence() { asm volatile("wgmma.fence.sync.aligned;" ::: "memory"); }
__device__ __forceinline__ void wgmma_commit() { asm volatile("wgmma.commit_group.sync.aligned;" ::: "memory"); }
template <int N> __device__ __forceinline__ void wgmma_wait() { asm volatile("wgmma.wait_group.sync.aligned %0;" :: "n"(N) : "memory"); }
__device__ __forceinline__ void bar_sync(int id, int n) { asm volatile("bar.sync %0, %1;" :: "r"(id), "r"(n) : "memory"); }
__device__ __forceinline__ void bar_arrive(int id, int n) { asm volatile("bar.arrive %0, %1;" :: "r"(id), "r"(n) : "memory"); }
__device__ __forceinline__ int uni(int v) { return __shfl_sync(0xffffffffu, v, 0); }

__device__ __forceinline__ void ldsm_x4_t(uint32_t (&r)[4], uint32_t addr) {
    asm volatile("ldmatrix.sync.aligned.m8n8.x4.trans.shared.b16 {%0,%1,%2,%3}, [%4];"
                 : "=r"(r[0]), "=r"(r[1]), "=r"(r[2]), "=r"(r[3]) : "r"(addr) : "memory");
}
__device__ __forceinline__ void stsm_x4_t(uint32_t addr, uint32_t r0, uint32_t r1, uint32_t r2, uint32_t r3) {
    asm volatile("stmatrix.sync.aligned.m8n8.x4.trans.shared.b16 [%0], {%1,%2,%3,%4};"
                 :: "r"(addr), "r"(r0), "r"(r1), "r"(r2), "r"(r3) : "memory");
}
__device__ __forceinline__ uint32_t movm(uint32_t a) {
    uint32_t d; asm volatile("movmatrix.sync.aligned.m8n8.trans.b16 %0, %1;" : "=r"(d) : "r"(a)); return d;
}
__device__ __forceinline__ uint32_t lds32(uint32_t addr) {
    uint32_t v; asm volatile("ld.shared.u32 %0, [%1];" : "=r"(v) : "r"(addr) : "memory"); return v;
}
__device__ __forceinline__ uint2 lds64(uint32_t addr) {
    uint2 v; asm volatile("ld.shared.v2.u32 {%0,%1}, [%2];" : "=r"(v.x), "=r"(v.y) : "r"(addr) : "memory"); return v;
}
__device__ __forceinline__ uint4 lds128(uint32_t addr) {
    uint4 v; asm volatile("ld.shared.v4.u32 {%0,%1,%2,%3}, [%4];" : "=r"(v.x), "=r"(v.y), "=r"(v.z), "=r"(v.w) : "r"(addr) : "memory"); return v;
}
__device__ __forceinline__ void sts64(uint32_t addr, uint32_t a, uint32_t b) {
    asm volatile("st.shared.v2.u32 [%0], {%1,%2};" :: "r"(addr), "r"(a), "r"(b) : "memory");
}
__device__ __forceinline__ void sts128(uint32_t addr, uint32_t a, uint32_t b, uint32_t c, uint32_t d) {
    asm volatile("st.shared.v4.u32 [%0], {%1,%2,%3,%4};" :: "r"(addr), "r"(a), "r"(b), "r"(c), "r"(d) : "memory");
}
__device__ __forceinline__ void ldg128(uint32_t* r, const char* p) {
    asm volatile("ld.global.v4.u32 {%0,%1,%2,%3}, [%4];" : "=r"(r[0]), "=r"(r[1]), "=r"(r[2]), "=r"(r[3]) : "l"(p) : "memory");
}
__device__ __forceinline__ void ldg64_stream_if(uint32_t& a, uint32_t& b, const char* p, bool v) {
    asm volatile("{\n\t.reg .pred p;\n\tsetp.ne.u32 p, %3, 0;\n\t@p ld.global.nc.L1::no_allocate.v2.u32 {%0,%1}, [%2];\n\t}"
                 : "+r"(a), "+r"(b) : "l"(p), "r"((uint32_t)v) : "memory");
}
__device__ __forceinline__ int4 ldg_stream(const int4* p) {
    int4 v;
    asm volatile("ld.volatile.global.v4.s32 {%0,%1,%2,%3}, [%4];" : "=r"(v.x), "=r"(v.y), "=r"(v.z), "=r"(v.w) : "l"(p) : "memory");
    return v;
}

__device__ __forceinline__ void mma_k16(float* d, uint32_t a0, uint32_t a1, uint32_t a2, uint32_t a3, uint32_t b0, uint32_t b1,
                                        float c0, float c1, float c2, float c3) {
    asm volatile("mma.sync.aligned.m16n8k16.row.col.f32.bf16.bf16.f32 {%0,%1,%2,%3}, {%4,%5,%6,%7}, {%8,%9}, {%10,%11,%12,%13};"
                 : "=f"(d[0]), "=f"(d[1]), "=f"(d[2]), "=f"(d[3])
                 : "r"(a0), "r"(a1), "r"(a2), "r"(a3), "r"(b0), "r"(b1), "f"(c0), "f"(c1), "f"(c2), "f"(c3));
}
__device__ __forceinline__ uint64_t desc_sw128(uint32_t saddr) {
    return (uint64_t)((saddr & 0x3FFFF) >> 4) | (1ull << 16) | (64ull << 32) | (1ull << 62);
}
template <int SCALE_D>
__device__ __forceinline__ void wgmma_n80(float (&d)[40], uint64_t da, uint64_t db) {
    asm volatile(
        "wgmma.mma_async.sync.aligned.m64n80k16.f32.bf16.bf16 "
        "{%0,%1,%2,%3,%4,%5,%6,%7,%8,%9,%10,%11,%12,%13,%14,%15,"
        "%16,%17,%18,%19,%20,%21,%22,%23,%24,%25,%26,%27,%28,%29,%30,%31,"
        "%32,%33,%34,%35,%36,%37,%38,%39}, "
        "%40, %41, %42, 1, 1, 1, 0;"
        : "+f"(d[0]), "+f"(d[1]), "+f"(d[2]), "+f"(d[3]), "+f"(d[4]), "+f"(d[5]), "+f"(d[6]), "+f"(d[7]),
          "+f"(d[8]), "+f"(d[9]), "+f"(d[10]), "+f"(d[11]), "+f"(d[12]), "+f"(d[13]), "+f"(d[14]), "+f"(d[15]),
          "+f"(d[16]), "+f"(d[17]), "+f"(d[18]), "+f"(d[19]), "+f"(d[20]), "+f"(d[21]), "+f"(d[22]), "+f"(d[23]),
          "+f"(d[24]), "+f"(d[25]), "+f"(d[26]), "+f"(d[27]), "+f"(d[28]), "+f"(d[29]), "+f"(d[30]), "+f"(d[31]),
          "+f"(d[32]), "+f"(d[33]), "+f"(d[34]), "+f"(d[35]), "+f"(d[36]), "+f"(d[37]), "+f"(d[38]), "+f"(d[39])
        : "l"(da), "l"(db), "n"(SCALE_D));
}
__device__ __forceinline__ void node_gemm(float (&d)[40], uint32_t wa, uint32_t xa) {
    const uint64_t da = desc_sw128(wa), db = desc_sw128(xa);
    wgmma_n80<0>(d, da, db);
    wgmma_n80<1>(d, da + 128, db + 2);
    wgmma_n80<1>(d, da + 256, db + 4);
    wgmma_n80<1>(d, da + 384, db + 6);
}
template <int NREG>
__device__ __forceinline__ void reg_fence(float (&d)[NREG]) {
    #pragma unroll
    for (int i = 0; i < NREG; i++) asm volatile("" : "+f"(d[i]) :: "memory");
}

__device__ __forceinline__ uint32_t pack_bf16(float lo, float hi) {
    uint32_t d; asm("cvt.rn.bf16x2.f32 %0, %1, %2;" : "=r"(d) : "f"(hi), "f"(lo)); return d;
}
__device__ __forceinline__ uint32_t fma_bf2(uint32_t a, uint32_t b, uint32_t c) {
    uint32_t d; asm("fma.rn.bf16x2 %0, %1, %2, %3;" : "=r"(d) : "r"(a), "r"(b), "r"(c)); return d;
}
__device__ __forceinline__ uint32_t add_bf2(uint32_t a, uint32_t b) {
    uint32_t d; asm("add.rn.bf16x2 %0, %1, %2;" : "=r"(d) : "r"(a), "r"(b)); return d;
}
__device__ __forceinline__ float ex2f(float x) {
    float y; asm("ex2.approx.ftz.f32 %0, %1;" : "=f"(y) : "f"(x)); return y;
}
__device__ __forceinline__ float rcpf(float x) {
    float y; asm("rcp.approx.ftz.f32 %0, %1;" : "=f"(y) : "f"(x)); return y;
}
__device__ __forceinline__ uint32_t fma_relu_bf2(uint32_t a, uint32_t b, uint32_t c) {
    uint32_t d; asm("fma.rn.relu.bf16x2 %0, %1, %2, %3;" : "=r"(d) : "r"(a), "r"(b), "r"(c)); return d;
}
__device__ __forceinline__ uint32_t gate_pair(float y0, float y1, uint32_t neb, uint32_t niea) {
    const uint32_t na = fma_bf2(pack_bf16(ex2f(y0), ex2f(y1)), neb, niea);
    const uint32_t r0 = ~na;
    const uint32_t e  = fma_relu_bf2(na, r0, 0x40EF40EFu);
    return fma_bf2(r0, e, r0);
}

__device__ __forceinline__ uint4 ld_relaxed_128(const uint4* p) {
    unsigned __int128 t;
    asm volatile("ld.relaxed.gpu.global.b128 %0, [%1];" : "=q"(t) : "l"(p) : "memory");
    return make_uint4((uint32_t)t, (uint32_t)(t >> 32), (uint32_t)(t >> 64), (uint32_t)(t >> 96));
}
__device__ __forceinline__ void st_relaxed_128(uint4* p, uint4 v) {
    const unsigned __int128 t = (unsigned __int128)(((uint64_t)v.w << 32) | v.z) << 64 | (((uint64_t)v.y << 32) | v.x);
    asm volatile("st.relaxed.gpu.global.b128 [%0], %1;" :: "l"(p), "q"(t) : "memory");
}
__device__ __forceinline__ void sts32(uint32_t addr, uint32_t a) { asm volatile("st.shared.u32 [%0], %1;" :: "r"(addr), "r"(a) : "memory"); }
__device__ __forceinline__ uint32_t atoms_inc_if(uint32_t addr, bool p, uint32_t dflt) {
    uint32_t r = dflt;
    asm volatile("{\n\t.reg .pred p;\n\tsetp.ne.u32 p, %2, 0;\n\t@p atom.shared.inc.u32 %0, [%1], 0x7FFFFFFF;\n\t}"
                 : "+r"(r) : "r"(addr), "r"((uint32_t)p) : "memory");
    return r;
}
__device__ __forceinline__ uint32_t atoms_inc(uint32_t addr) {
    uint32_t r; asm volatile("atom.shared.add.u32 %0, [%1], 1;" : "=r"(r) : "r"(addr) : "memory"); return r;
}

__global__ void __launch_bounds__(NTHREADS, 1)
gatedgcn_kernel(const __nv_bfloat16* __restrict__ x, const __nv_bfloat16* __restrict__ e_attr,
                const int* __restrict__ src, const int* __restrict__ dst,
                const __nv_bfloat16* __restrict__ w_a, const __nv_bfloat16* __restrict__ w_b,
                const __nv_bfloat16* __restrict__ w_c, const __nv_bfloat16* __restrict__ w_u,
                const __nv_bfloat16* __restrict__ w_v, __nv_bfloat16* __restrict__ out) {
    extern __shared__ __align__(1024) unsigned char smem[];
    const uint32_t sb = (uint32_t)__cvta_generic_to_shared(smem);
    const int tid = threadIdx.x, lane = tid & 31;
    const int warp = uni(tid >> 5);
    const int cta = blockIdx.x;
    const int node0 = cta * NPB;
    const int g = lane >> 2, q = lane & 3;

    int* s_cnt  = (int*)(smem + SM_CNT);
    int* s_ncnt = (int*)(smem + SM_NCNT);
    volatile int* s_misc = (volatile int*)(smem + SM_MISC);

    auto load_weights = [&](int t, int nt) {
        #pragma unroll 1
        for (int i = t; i < 512; i += nt) {
            const uint32_t so = sb + SM_W + (i >> 3) * 128 + (((i ^ (i >> 3)) & 7) << 4);
            cp_async16(so + WS_B, w_b + i * 8);
            cp_async16(so + WS_V, w_v + i * 8);
            cp_async16(so + WS_A, w_a + i * 8);
            cp_async16(so + WS_U, w_u + i * 8);
        }
        if (t < 128) cp_async16(sb + SM_W + WS_C + (t >> 3) * 128 + (((t ^ (t >> 3)) & 7) << 4), w_c + t * 8);
    };

    auto store_rows = [&](const float (&d)[40], uint32_t base, int ld) {
        base += ((lane & 7) + ((lane >> 4) << 3)) * ld + ((warp & 3) * 16 + ((lane >> 3) & 1) * 8) * 2;
        #pragma unroll
        for (int w = 0; w < 10; w += 2)
            stsm_x4_t(base + w * 8 * ld,
                      pack_bf16(d[4 * w + 0], d[4 * w + 1]), pack_bf16(d[4 * w + 2], d[4 * w + 3]),
                      pack_bf16(d[4 * w + 4], d[4 * w + 5]), pack_bf16(d[4 * w + 6], d[4 * w + 7]));
    };
    auto neg_exp = [&](float (&d)[40], float scale, float bias, int slot) {
        float mx = 0.f;
        #pragma unroll
        for (int i = 0; i < 40; i++) { mx = fmaxf(mx, fabsf(d[i])); d[i] = -ex2f(fmaf(d[i], scale, bias)); }
        const uint32_t mb = __reduce_max_sync(0xffffffffu, __float_as_uint(mx));
        if (lane == 0) atomicMax((unsigned int*)&s_misc[slot], mb);
    };
    if (warp < NET / 32) {
        const int ebase = cta * CHUNK;
        const int nvec = (min(CHUNK, N_EDGES - ebase)) >> 2;
        const int sg = tid / UMAIN, su = tid - sg * UMAIN;
        const bool act_last = sg + (UPT - 1) * SPP < NB;
        int4 dv[4], sv[4];
        bool has[4];
        #pragma unroll
        for (int k = 0; k < 4; k++) {
            const int o = tid + (k & 1) * NET, v = (k >> 1) * WVEC + o;
            has[k] = o < WVEC && v < nvec;
            if (k == 2) {
                if (tid < 272 + 80 + 4 && tid != 272 + 80) s_cnt[tid] = 0;
                bar_sync(1, NET);
            }
            if (k >= 2) has[k] = has[k] && (dv[0].x | sv[0].x | (has[1] ? dv[1].x | sv[1].x : 0)) >= 0;
            if (has[k]) {
                dv[k] = ldg_stream((const int4*)(dst + ebase) + v);
                sv[k] = ldg_stream((const int4*)(src + ebase) + v);
            }
        }
        uint32_t tag = 0;
        #pragma unroll
        for (int w = 0; w < 2; w++) {
            if (w == 1) bar_sync(1, NET);
            #pragma unroll
            for (int k = 2 * w; k < 2 * w + 2; k++) {
                if (has[k]) {
                    const int v = tid + (k & 1) * NET;
                    const int dd[4] = {dv[k].x, dv[k].y, dv[k].z, dv[k].w};
                    const int ss[4] = {sv[k].x, sv[k].y, sv[k].z, sv[k].w};
                    uint32_t b[4], rank[4];
                    #pragma unroll
                    for (int j = 0; j < 4; j++) { b[j] = (uint32_t)dd[j] / NPB; rank[j] = (uint32_t)atomicAdd(&s_cnt[w * 136 + b[j]], 1); }
                    #pragma unroll
                    for (int j = 0; j < 4; j++) {
                        const uint32_t rec = (((uint32_t)(v * 4 + j) - b[j]) * NPB + (uint32_t)dd[j]) * N_NODES + (uint32_t)ss[j];
                        sts32(sb + SM_STAGE + (b[j] * SEG_LD + min(rank[j], (uint32_t)SEGCAP)) * 4, rec);
                    }
                }
            }
            if (w == 0) { bar_sync(8, NET + 32); tag = ((uint32_t)s_misc[0] + 1u) & 0xFFFFFFu; }
            else bar_sync(1, NET);
            {
                const uint32_t a = sb + SM_STAGE + (sg * SEG_LD + 4 * su) * 4;
                uint4* gq = g_seg + (size_t)w * 2 * TAIL + ((size_t)sg * NB + cta) * UMAIN + su;
                uint32_t tmask = 0;
                uint4 pu[UPT];
                #pragma unroll
                for (int k = 0; k < UPT; k++) {
                    const bool on = k < UPT - 1 || act_last;
                    const int cnt = on ? s_cnt[w * 136 + sg + k * SPP] : 0, n = cnt - 4 * su;
                    const uint4 v = lds128(on ? a + k * SPP * SEG_LD * 4 : a);
                    pu[k].x = (n > 0 ? v.x : REC_NONE) | tag << 31;
                    pu[k].y = (n > 1 ? v.y : REC_NONE) | (tag >> 1) << 31;
                    pu[k].z = (n > 2 ? v.z : REC_NONE) | (tag >> 2) << 31;
                    pu[k].w = cnt > SEGCAP ? REC_OVF : (n > 3 ? v.w : REC_NONE) | (cnt > 4 * UMAIN + 3 * su ? 0x80000000u : 0u);
                    if (cnt > 4 * UMAIN + 3 * (su & ~1) && cnt <= SEGCAP) tmask |= 1u << k;
                }
                #pragma unroll
                for (int k = 0; k < UPT; k++)
                    if (k < UPT - 1 || act_last) st_relaxed_128(gq + (size_t)k * SPP * NB * UMAIN, pu[k]);
                while (tmask) {
                    const int k = __ffs(tmask) - 1;
                    tmask &= tmask - 1;
                    const uint32_t ta = a + (k * SPP * SEG_LD + 4 * UMAIN - su) * 4;
                    const int n = s_cnt[w * 136 + sg + k * SPP] - 4 * UMAIN - 3 * su;
                    st_relaxed_128(gq + (size_t)k * SPP * NB * UMAIN + TAIL,
                                   make_uint4(n > 0 ? lds32(ta) : REC_NONE, n > 1 ? lds32(ta + 4) : REC_NONE, n > 2 ? lds32(ta + 8) : REC_NONE, REC_NONE | tag));
                }
            }
        }
        const uint4* gp = g_seg + (size_t)cta * NB * UMAIN + tid;
        const uint32_t dcnt = sb + SM_DCNT + lane * 4, dump = sb + SM_DUMP + lane * 8 - CAPN * 8;
        const uint4 none = make_uint4(REC_NONE | tag << 31, REC_NONE | (tag >> 1) << 31, REC_NONE | (tag >> 2) << 31, REC_NONE | tag);
        uint4 rec[2 * UPT];
        auto fetch = [&](int w) {
            #pragma unroll
            for (int k = 0; k < UPT; k++) {
                rec[w * UPT + k] = none;
                if (k < UPT - 1 || act_last) rec[w * UPT + k] = ld_relaxed_128(gp + w * 2 * TAIL + k * SPP * UMAIN);
            }
        };
        fetch(0);
        bar_sync(3, NTHREADS);
        bool first = true;
        uint32_t todo = 3;
        #pragma unroll 1
        while (todo) {
            #pragma unroll
            for (int w = 0; w < 2; w++) {
                if (!(todo >> w & 1)) continue;
                bool more = false;
                for (int tries = 0;; tries++) {
                    bool ok = true;
                    #pragma unroll
                    for (int k = 0; k < UPT; k++) {
                        uint4& u = rec[w * UPT + k];
                        const bool stale = first ? (int)((u.x ^ none.x) | (u.y ^ none.y) | (u.z ^ none.z)) < 0 : u.w != none.w;
                        if (stale) { u = ld_relaxed_128(gp + w * 2 * TAIL + k * SPP * UMAIN); ok = false; }
                    }
                    if (__all_sync(0xffffffffu, ok)) break;
                    if (tries > 400000) {
                        s_misc[1] = 1;
                        #pragma unroll
                        for (int k = 0; k < UPT; k++) rec[w * UPT + k] = none;
                    }
                }
                uint32_t sv_[UPT][4], el[UPT][4], la[UPT][4], r[UPT][4];
                #pragma unroll
                for (int k = 0; k < UPT; k++) {
                    uint4& u = rec[w * UPT + k];
                    const uint32_t rw[4] = {u.x & 0x7FFFFFFFu, u.y & 0x7FFFFFFFu, u.z & 0x7FFFFFFFu, u.w & 0x7FFFFFFFu};
                    #pragma unroll
                    for (int j = 0; j < 4; j++) {
                        const uint32_t t = rw[j] / N_NODES;
                        el[k][j] = t / NPB;
                        const uint32_t dl = t - el[k][j] * NPB;
                        sv_[k][j] = (rw[j] - t * N_NODES) << 8;
                        const bool valid = rw[j] < REC_OVF;
                        la[k][j] = valid ? sb + SM_LIST + dl * LIST_LD : dump;
                        r[k][j] = atoms_inc(valid ? sb + SM_NCNT + dl * 4 : dcnt);
                    }
                    if (u.w == REC_OVF) s_misc[1] = 1;
                    const bool tl = (int)u.w < 0;
                    u = none;
                    if (tl) { u = ld_relaxed_128(gp + w * 2 * TAIL + k * SPP * UMAIN + TAIL); more = true; }
                }
                if (!__any_sync(0xffffffffu, more)) todo &= ~(1u << w);
                #pragma unroll
                for (int k = 0; k < UPT; k++)
                    #pragma unroll
                    for (int j = 0; j < 4; j++)
                        sts64(la[k][j] + min(r[k][j], (uint32_t)CAPN) * 8, sv_[k][j], ((sg + k * SPP) * CHUNK + w * (CHUNK / 2) + el[k][j]) * 32u);
                if (w == 0 && first) fetch(1);
            }
            first = false;
            gp += TAIL;
        }
    } else {
        const int wtid = tid - NET;
        uint32_t epoch = 0;
        if (wtid == 96) epoch = *(volatile unsigned int*)&g_epoch[cta * 8];
        {
            const uint32_t so = (wtid >> 3) * 128 + (((wtid ^ (wtid >> 3)) & 7) << 4);
            #pragma unroll
            for (int k = 0; k < 5; k++) {
                const int r = (wtid >> 3) + 16 * k;
                const bool ok = r < NPB && node0 + r < N_NODES;
                cp_async16_zfill(sb + SM_XOWN + so + k * 2048, x + (ok ? (size_t)node0 * 64 + wtid * 8 + k * 1024 : 0), ok ? 16 : 0);
            }
            #pragma unroll
            for (int k = 0; k < 4; k++) {
                cp_async16(sb + SM_W + WS_V + so + k * 2048, w_v + wtid * 8 + k * 1024);
                cp_async16(sb + SM_W + WS_B + so + k * 2048, w_b + wtid * 8 + k * 1024);
            }
            cp_commit();
            #pragma unroll
            for (int k = 0; k < 4; k++) {
                cp_async16(sb + SM_W + WS_A + so + k * 2048, w_a + wtid * 8 + k * 1024);
                cp_async16(sb + SM_W + WS_U + so + k * 2048, w_u + wtid * 8 + k * 1024);
            }
            cp_async16(sb + SM_W + WS_C + so, w_c + wtid * 8);
            cp_commit();
        }
        if (wtid >= 96) {
            if (lane == 0) { s_misc[0] = (int)epoch; g_epoch[cta * 8] = epoch + 1u; }
            __syncwarp();
            bar_arrive(8, NET + 32);
        }
        if (wtid < 8) sts128(sb + SM_LIST + NULLT + wtid * 16, NULL_W0, 0u, NULL_W0, 0u);
        if (wtid >= 8 && wtid < 12) s_misc[wtid - 4] = 0;
        if (wtid >= 32 && wtid < 96) s_misc[wtid - 24] = wtid < 64 ? 0 : CAPN;
        cp_wait<1>();
        fence_async();
        bar_sync(2, 128);
        {
            float db[40], dv[40];
            wgmma_fence();
            node_gemm(dv, sb + SM_W + WS_V, sb + SM_XOWN);
            wgmma_commit();
            node_gemm(db, sb + SM_W + WS_B, sb + SM_XOWN);
            wgmma_commit();
            wgmma_wait<1>();
            reg_fence(dv);
            store_rows(dv, sb + SM_T + 128, T_LD);
            float mv = 0.f;
            #pragma unroll
            for (int i = 0; i < 40; i++) mv = fmaxf(mv, fabsf(dv[i]));
            if (mv > 1e9f) s_misc[5] = 0x7F800000;
            wgmma_wait<0>();
            reg_fence(db);
            neg_exp(db, -L2E, 0.f, 5);
            store_rows(db, sb + SM_T, T_LD);
        }
        bar_sync(2, 128);
        {
            uint4 v[10];
            #pragma unroll
            for (int k = 0; k < 10; k++)
                v[k] = lds128(sb + SM_T + ((wtid >> 4) + 8 * k) * T_LD + (wtid & 1) * 128 + ((wtid >> 1) & 7) * 16);
            #pragma unroll
            for (int k = 0; k < 10; k++) {
                const int r = (wtid >> 4) + 8 * k;
                if (node0 + r == N_NODES) v[k].x = v[k].y = v[k].z = v[k].w = (wtid & 1) ? 0u : 0xFF80FF80u;
                if (r < NPB && node0 + r <= N_NODES) g_tab[(size_t)node0 * 16 + wtid + k * 128] = v[k];
            }
        }
        cp_wait<0>();
        fence_async();
        bar_arrive(3, NTHREADS);
        bar_sync(2, 128);
        const uint32_t ftag = (uint32_t)s_misc[0] + 1u;
        {
            float da[40], du[40];
            wgmma_fence();
            node_gemm(du, sb + SM_W + WS_U, sb + SM_XOWN);
            node_gemm(da, sb + SM_W + WS_A, sb + SM_XOWN);
            wgmma_commit();
            if (wtid == 96)
                asm volatile("st.release.gpu.global.u64 [%0], %1;"
                             :: "l"(&g_flag[cta]), "l"(((unsigned long long)ftag << 32) | (uint32_t)s_misc[5]) : "memory");
            __syncwarp();
            wgmma_wait<0>();
            reg_fence(du);
            reg_fence(da);
            store_rows(du, sb + SM_U, U_LD);
            neg_exp(da, L2E, -USHIFT, 4);
            store_rows(da, sb + SM_IEA, U_LD);
        }
        if (wtid < 96) {
            #pragma unroll 2
            for (int i = wtid; i < 512; i += 96) {
                const int l = i >> 4, j = (i >> 1) & 7, h = i & 1;
                const int f = 32 * (j >> 2) + 8 * (l >> 3) + 2 * (j & 3) + ((l >> 2) & 1);
                const int r = 4 * (l & 3) + 2 * h;
                const unsigned char* wc = smem + SM_W + WS_C + (f & 7) * 2;
                const float c0 = __bfloat162float(*(const __nv_bfloat16*)(wc + r * 128 + (((f >> 3) ^ (r & 7)) << 4)));
                const float c1 = __bfloat162float(*(const __nv_bfloat16*)(wc + (r + 1) * 128 + (((f >> 3) ^ ((r + 1) & 7)) << 4)));
                ((uint32_t*)(smem + SM_WCF))[((i >> 2) & 3) * 128 + l * 4 + (i & 3)] = pack_bf16(c0 * -L2E, c1 * -L2E);
            }
            unsigned long long f0 = (unsigned long long)ftag << 32, f1 = f0;
            for (int tries = 0;; tries++) {
                if (wtid < NB / 2)
                    asm volatile("ld.acquire.gpu.global.v2.u64 {%0,%1}, [%2];" : "=l"(f0), "=l"(f1) : "l"(g_flag + 2 * wtid) : "memory");
                if (__all_sync(0xffffffffu, (uint32_t)(f0 >> 32) == ftag && (uint32_t)(f1 >> 32) == ftag)) break;
                if (tries > 100000) { f0 = 0x7F800000u; break; }
            }
            const uint32_t mx = __reduce_max_sync(0xffffffffu, max((uint32_t)f0, (uint32_t)f1));
            if (lane == 0) atomicMax((unsigned int*)&s_misc[6], mx);
        }
    }
    __syncthreads();
    const bool bad_list = s_misc[1] != 0 ||
        __any_sync(0xffffffffu, max(max(s_ncnt[lane], s_ncnt[lane + 32]), s_ncnt[min(lane + 64, NPB - 1)]) > CAPN);

    auto reduce_rows = [&](float (&sum)[4], const uint32_t (&den)[8], const uint32_t (&num)[8]) {
        float s1[4] = {0.f, 0.f, 0.f, 0.f}, s2[4] = {0.f, 0.f, 0.f, 0.f};
        uint32_t ln;
        asm volatile("mov.u32 %0, %%laneid;" : "=r"(ln));
        #pragma unroll
        for (int j = 0; j < 4; j++) {
            const uint32_t sel = ((ln >> 2) & 3) == j ? 0x3F803F80u : 0u;
            mma_k16(s1, sel, 0u, 0u, sel, movm(den[j]), movm(num[j]), s1[0], s1[1], s1[2], s1[3]);
            mma_k16(s2, sel, 0u, 0u, sel, movm(den[j + 4]), movm(num[j + 4]), s2[0], s2[1], s2[2], s2[3]);
        }
        #pragma unroll
        for (int i = 0; i < 4; i++) sum[i] = ln < 16 ? s1[i] : s2[i];
    };
    auto write_node = [&](int node, const float (&sum)[4], int f0) {
        if (node0 + node < N_NODES) {
            const uint32_t iw = lds32(sb + SM_IEA + node * U_LD + f0 * 2);
            const uint32_t uw = lds32(sb + SM_U + node * U_LD + f0 * 2);
            const uint32_t xw = lds32(sb + SM_XOWN + node * 128 + (((f0 >> 3) ^ (node & 7)) << 4) + (f0 & 7) * 2);
            const float i0 = __uint_as_float(iw << 16), i1 = __uint_as_float(iw & 0xFFFF0000u);
            const float z0 = __uint_as_float(uw << 16) + sum[2] * i0 * rcpf(fmaf(sum[0], i0, -RSCALE * 1e-6f));
            const float z1 = __uint_as_float(uw & 0xFFFF0000u) + sum[3] * i1 * rcpf(fmaf(sum[1], i1, -RSCALE * 1e-6f));
            const float o0 = __uint_as_float(xw << 16) + fmaxf(z0, 0.f);
            const float o1 = __uint_as_float(xw & 0xFFFF0000u) + fmaxf(z1, 0.f);
            *(uint32_t*)(out + (size_t)(node0 + node) * 64 + f0) = pack_bf16(o0, o1);
        }
    };
    const char* eq = (const char*)e_attr + q * 8;
    const uint32_t la = sb + SM_LIST + g * 8;
    const bool fast = !bad_list && __int_as_float(s_misc[4]) <= RANGE_A && __int_as_float(s_misc[4]) + __int_as_float(s_misc[6]) <= RANGE_AB;

    if (fast) {
        auto job_range = [&](int j, int& tb, int& te) {
            tb = NULLT; te = NULLT + 128;
            if (j >= NJOBS) return -1;
            const int n = j < NWHOLE ? j : NWHOLE + ((j - NWHOLE) >> 1);
            const int cnt = s_ncnt[n];
            const int nt = max(1, (cnt + 15) >> 4);
            if (cnt + lane < nt * 16) sts64(sb + SM_LIST + n * LIST_LD + (cnt + lane) * 8, NULL_W0, 0u);
            __syncwarp();
            const int mid = j < NWHOLE ? nt : (nt + 1) >> 1;
            const bool second = j >= NWHOLE && ((j - NWHOLE) & 1);
            if (!second) { tb = n * LIST_LD; te = tb + mid * 128; }
            else if (mid < nt) { tb = n * LIST_LD + mid * 128; te = n * LIST_LD + nt * 128; }
            return n;
        };
        const char* tabq = (const char*)g_tab + q * 32;
        asm volatile("" : "+l"(tabq));
        uint32_t wcf[16];
        #pragma unroll
        for (int i = 0; i < 4; i++) {
            const uint4 v = lds128(sb + SM_WCF + i * 512 + lane * 16);
            wcf[4 * i] = v.x; wcf[4 * i + 1] = v.y; wcf[4 * i + 2] = v.z; wcf[4 * i + 3] = v.w;
        }
        uint32_t eb[2][8], hq[2][8], ev[4] = {0u, 0u, 0u, 0u};
        const char *p0, *p1;
        bool v0, v1;
        auto load_rec = [&](int tt) {
            const uint2 r0 = lds64(la + tt), r1 = lds64(la + tt + 64);
            p0 = tabq + r0.x; p1 = tabq + r1.x;
            v0 = r0.x != NULL_W0; v1 = r1.x != NULL_W0;
            ldg64_stream_if(ev[0], ev[2], eq + r0.y, v0);
            ldg64_stream_if(ev[1], ev[3], eq + r1.y, v1);
        };
        auto load_half = [&](int h) {
            ldg128(&eb[0][4 * h], p0 + 128 * h); ldg128(&eb[1][4 * h], p1 + 128 * h);
            ldg128(&hq[0][4 * h], p0 + 16 + 128 * h); ldg128(&hq[1][4 * h], p1 + 16 + 128 * h);
        };
        auto load_rows = [&]() { load_half(0); load_half(1); };
        const int yes = s_misc[1] == 0;
        int t, te;
        int node = job_range(warp, t, te);
        load_rec(t);
        load_rows();
        while (true) {
            int nnode = 0;
            uint32_t iea[8], den[8], num[8];
            {
                const uint4 w0 = lds128(sb + SM_IEA + node * U_LD + q * 16), w1 = lds128(sb + SM_IEA + node * U_LD + 64 + q * 16);
                iea[0] = w0.x; iea[1] = w0.y; iea[2] = w0.z; iea[3] = w0.w; iea[4] = w1.x; iea[5] = w1.y; iea[6] = w1.z; iea[7] = w1.w;
            }
            #pragma unroll
            for (int j = 0; j < 8; j++) { den[j] = 0u; num[j] = 0u; }
            bool last;
            do {
                const uint32_t a0 = v0 ? ev[0] : 0u, a1 = v1 ? ev[1] : 0u, a2 = v0 ? ev[2] : 0u, a3 = v1 ? ev[3] : 0u;
                const bool upper = __any_sync(0xffffffffu, v1);
                t += 128;
                last = t == te;
                if (last) nnode = job_range(uni((int)atoms_inc_if(sb + SM_MISC + 12, lane == 0, 0u)) + NWARPS, t, te);
                load_rec(t);
                if (upper) {
                    #pragma unroll
                    for (int h = 0; h < 2; h++) {
                        if (h == 1) { int y = yes; asm volatile("" : "+r"(y) :: "memory"); if (!y) break; }
                        float d[16];
                        #pragma unroll
                        for (int j = 0; j < 4; j++)
                            mma_k16(&d[4 * j], a0, a1, a2, a3, wcf[8 * h + 2 * j], wcf[8 * h + 2 * j + 1], -USHIFT, -USHIFT, -USHIFT, -USHIFT);
                        #pragma unroll
                        for (int jj = 0; jj < 4; jj++) {
                            const int j = 4 * h + jj;
                            const uint32_t ra = gate_pair(d[4 * jj], d[4 * jj + 1], eb[0][j], iea[j]);
                            const uint32_t rb = gate_pair(d[4 * jj + 2], d[4 * jj + 3], eb[1][j], iea[j]);
                            den[j] = add_bf2(add_bf2(den[j], ra), rb);
                            num[j] = fma_bf2(rb, hq[1][j], fma_bf2(ra, hq[0][j], num[j]));
                        }
                        load_half(h);
                    }
                } else {
                    #pragma unroll
                    for (int j = 0; j < 8; j++) {
                        float d[4];
                        mma_k16(d, a0, a1, a2, a3, wcf[2 * j], wcf[2 * j + 1], -USHIFT, -USHIFT, -USHIFT, -USHIFT);
                        const uint32_t ra = gate_pair(d[0], d[1], eb[0][j], iea[j]);
                        den[j] = add_bf2(den[j], ra);
                        num[j] = fma_bf2(ra, hq[0][j], num[j]);
                    }
                    load_rows();
                }
            } while (!last);
            const int f0 = 32 * (g >> 2) + 8 * q + 2 * (g & 3);
            float sum[4];
            reduce_rows(sum, den, num);
            bool mine = true;
            if (node >= NWHOLE) {
                const uint32_t st = sb + SM_STATE + (node - NWHOLE) * 4, pa = sb + SM_PART + (node - NWHOLE) * 512 + lane * 16;
                mine = uni((int)atoms_inc_if(st, lane == 0, 0u)) != 0;
                if (!mine) {
                    sts128(pa, __float_as_uint(sum[0]), __float_as_uint(sum[1]), __float_as_uint(sum[2]), __float_as_uint(sum[3]));
                    asm volatile("fence.acq_rel.cta;" ::: "memory");
                    __syncwarp();
                    if (lane == 0) atomicAdd((int*)(smem + (st - sb)), 2);
                } else {
                    while (*(volatile int*)(smem + (st - sb)) < 4) {}
                    asm volatile("fence.acq_rel.cta;" ::: "memory");
                    const uint4 o = lds128(pa);
                    sum[0] += __uint_as_float(o.x); sum[1] += __uint_as_float(o.y);
                    sum[2] += __uint_as_float(o.z); sum[3] += __uint_as_float(o.w);
                }
            }
            if (mine) write_node(node, sum, f0);
            if (nnode < 0) break;
            node = nnode;
        }
    } else {
        float2* acc = g_acc + (size_t)cta * NPB * 64;
        __syncthreads();
        load_weights(tid, NTHREADS);
        cp_commit();
        for (int i = tid; i < NPB * 64; i += NTHREADS) acc[i] = make_float2(0.f, 0.f);
        cp_wait<0>();
        int scan_pos = bad_list ? 0 : N_EDGES;
        int pend = 0, pv = 0;
        int4 d4 = make_int4(0, 0, 0, 0);
        bool more = true;
        while (more) {
            if (bad_list) {
                __syncthreads();
                if (tid < 80) s_ncnt[tid] = 0;
                __syncthreads();
                while (true) {
                    const int dd[4] = {d4.x, d4.y, d4.z, d4.w};
                    #pragma unroll
                    for (int j = 0; j < 4; j++) {
                        if (pend >> j & 1) {
                            const int dl = dd[j] - node0;
                            const int r = atomicAdd(&s_ncnt[dl], 1);
                            if (r < CAPN) {
                                const int e = pv * 4 + j;
                                sts64(sb + SM_LIST + dl * LIST_LD + r * 8, (uint32_t)__ldg(src + e) << 8, (uint32_t)e * 32u);
                                pend &= ~(1 << j);
                            }
                        }
                    }
                    if (__syncthreads_or(pend)) break;
                    if (scan_pos >= N_EDGES) { more = false; break; }
                    pv = (scan_pos >> 2) + tid;
                    if (pv < N_EDGES / 4) {
                        d4 = __ldg((const int4*)dst + pv);
                        pend = ((uint32_t)(d4.x - node0) < NPB ? 1 : 0) | ((uint32_t)(d4.y - node0) < NPB ? 2 : 0)
                             | ((uint32_t)(d4.z - node0) < NPB ? 4 : 0) | ((uint32_t)(d4.w - node0) < NPB ? 8 : 0);
                    }
                    scan_pos += NTHREADS * 4;
                }
            } else {
                more = false;
                __syncthreads();
            }
            const uint32_t wrow = sb + SM_W + (lane & 15) * 128;
            #pragma unroll 1
            for (int job = warp; job < NPB * 4; job += NWARPS) {
                const int n = job >> 2, jp = job & 3;
                const int cnt = min(s_ncnt[n], CAPN);
                if (cnt == 0) continue;
                const uint32_t wa = wrow + (((2 * jp + (lane >> 4)) ^ (lane & 7)) << 4);
                float ca[8] = {0.f, 0.f, 0.f, 0.f, 0.f, 0.f, 0.f, 0.f};
                #pragma unroll
                for (int k = 0; k < 4; k++) {
                    const uint32_t a0 = lds32(sb + SM_XOWN + n * 128 + (((2 * k) ^ (n & 7)) << 4) + q * 4);
                    const uint32_t a2 = lds32(sb + SM_XOWN + n * 128 + (((2 * k + 1) ^ (n & 7)) << 4) + q * 4);
                    uint32_t b[4];
                    ldsm_x4_t(b, wa + WS_A + k * 2048);
                    mma_k16(&ca[0], a0, a0, a2, a2, b[0], b[1], ca[0], ca[1], ca[2], ca[3]);
                    mma_k16(&ca[4], a0, a0, a2, a2, b[2], b[3], ca[4], ca[5], ca[6], ca[7]);
                }
                float sd[4] = {0.f, 0.f, 0.f, 0.f}, sn[4] = {0.f, 0.f, 0.f, 0.f};
                #pragma unroll 1
                for (int i0 = 0; i0 < cnt; i0 += 16) {
                    const bool v0 = i0 + g < cnt, v1 = i0 + g + 8 < cnt;
                    const uint2 r0 = lds64(sb + SM_LIST + n * LIST_LD + (v0 ? i0 + g : 0) * 8);
                    const uint2 r1 = lds64(sb + SM_LIST + n * LIST_LD + (v1 ? i0 + g + 8 : 0) * 8);
                    const uint32_t* x0 = (const uint32_t*)((const char*)x + (r0.x >> 1)) + q;
                    const uint32_t* x1 = (const uint32_t*)((const char*)x + (r1.x >> 1)) + q;
                    const uint32_t* e0 = (const uint32_t*)((const char*)e_attr + r0.y) + q;
                    const uint32_t* e1 = (const uint32_t*)((const char*)e_attr + r1.y) + q;
                    float gg[8], hh[8] = {0.f, 0.f, 0.f, 0.f, 0.f, 0.f, 0.f, 0.f};
                    uint32_t b[4];
                    {
                        const uint32_t a0 = __ldg(e0), a1 = __ldg(e1), a2 = __ldg(e0 + 4), a3 = __ldg(e1 + 4);
                        ldsm_x4_t(b, wa + WS_C);
                        mma_k16(&gg[0], a0, a1, a2, a3, b[0], b[1], ca[0], ca[1], ca[2], ca[3]);
                        mma_k16(&gg[4], a0, a1, a2, a3, b[2], b[3], ca[4], ca[5], ca[6], ca[7]);
                    }
                    #pragma unroll
                    for (int k = 0; k < 4; k++) {
                        const uint32_t a0 = __ldg(x0 + 8 * k), a1 = __ldg(x1 + 8 * k), a2 = __ldg(x0 + 8 * k + 4), a3 = __ldg(x1 + 8 * k + 4);
                        ldsm_x4_t(b, wa + WS_B + k * 2048);
                        mma_k16(&gg[0], a0, a1, a2, a3, b[0], b[1], gg[0], gg[1], gg[2], gg[3]);
                        mma_k16(&gg[4], a0, a1, a2, a3, b[2], b[3], gg[4], gg[5], gg[6], gg[7]);
                        ldsm_x4_t(b, wa + WS_V + k * 2048);
                        mma_k16(&hh[0], a0, a1, a2, a3, b[0], b[1], hh[0], hh[1], hh[2], hh[3]);
                        mma_k16(&hh[4], a0, a1, a2, a3, b[2], b[3], hh[4], hh[5], hh[6], hh[7]);
                    }
                    #pragma unroll
                    for (int i = 0; i < 8; i++) {
                        const float eta = ((i & 2) ? v1 : v0) ? 1.0f / (1.0f + ex2f(gg[i] * -L2E)) : 0.f;
                        const int o = (i >> 2) * 2 + (i & 1);
                        sd[o] += eta;
                        sn[o] = fmaf(eta, hh[i], sn[o]);
                    }
                }
                #pragma unroll
                for (int i = 0; i < 4; i++) {
                    #pragma unroll
                    for (int o = 4; o < 32; o <<= 1) {
                        sd[i] += __shfl_xor_sync(0xffffffffu, sd[i], o);
                        sn[i] += __shfl_xor_sync(0xffffffffu, sn[i], o);
                    }
                }
                if (g == 0) {
                    #pragma unroll
                    for (int i = 0; i < 4; i++) {
                        float2* pa = acc + n * 64 + jp * 16 + (i >> 1) * 8 + 2 * q + (i & 1);
                        *pa = make_float2(pa->x + sd[i], pa->y + sn[i]);
                    }
                }
            }
        }
        __syncthreads();
        for (int i = tid; i < NPB * 64; i += NTHREADS) {
            const int n = i >> 6, f = i & 63;
            if (node0 + n < N_NODES) {
                const float2 a = acc[i];
                const float u = __bfloat162float(*(const __nv_bfloat16*)(smem + SM_U + n * U_LD + f * 2));
                const float xv = __bfloat162float(*(const __nv_bfloat16*)(smem + SM_XOWN + n * 128 + (((f >> 3) ^ (n & 7)) << 4) + (f & 7) * 2));
                out[(size_t)(node0 + n) * 64 + f] = __float2bfloat16(xv + fmaxf(u + a.y / (a.x + 1e-6f), 0.f));
            }
        }
    }
}

}

extern "C" void kernel_launch(void* const* d_in, const int* in_sizes, int n_in, void* d_out, int out_size) {
    (void)in_sizes; (void)n_in; (void)out_size;
    constexpr int SMEM = SM_TOTAL;
    cudaFuncSetAttribute(gatedgcn_kernel, cudaFuncAttributeMaxDynamicSharedMemorySize, SMEM);
    gatedgcn_kernel<<<NB, NTHREADS, SMEM>>>(
        (const __nv_bfloat16*)d_in[0], (const __nv_bfloat16*)d_in[1], (const int*)d_in[2], (const int*)d_in[3],
        (const __nv_bfloat16*)d_in[4], (const __nv_bfloat16*)d_in[5], (const __nv_bfloat16*)d_in[6],
        (const __nv_bfloat16*)d_in[7], (const __nv_bfloat16*)d_in[8], (__nv_bfloat16*)d_out);
}
```

```cpp
#include <cuda_runtime.h>
#include <cuda_bf16.h>
#include <stdint.h>

namespace {

constexpr int N_NODES  = 10000;
constexpr int N_EDGES  = 640000;
constexpr int NB       = 132;
constexpr int NPB      = 76;
constexpr int CHUNK    = 4864;
constexpr int UMAIN    = 8;
constexpr int SEGCAP   = 7 * UMAIN;
constexpr int WVEC     = CHUNK / 8;
constexpr int SEG_LD   = SEGCAP + 4;
constexpr int CAPN     = 112;
constexpr int LIST_LD  = (CAPN + 1) * 8;
constexpr int NTHREADS = 512;
constexpr int NWARPS   = NTHREADS / 32;
constexpr int NET      = 384;
constexpr int NSPLIT   = 4;
constexpr int NWHOLE   = NPB - NSPLIT;
constexpr int NJOBS    = NWHOLE + 2 * NSPLIT;
constexpr int SPP      = NET / UMAIN;
constexpr int UPT      = (NB + SPP - 1) / SPP;
constexpr int TAIL     = NB * NB * UMAIN;
static_assert(UMAIN % 2 == 0 && NET % UMAIN == 0 && WVEC <= 2 * NET && SEG_LD % 4 == 0, "exchange geometry");
static_assert(NB * NPB > N_NODES && NB * CHUNK >= N_EDGES, "coverage");

constexpr int U_LD = 144;
constexpr int T_LD = 272;

constexpr int SM_XOWN  = 0;
constexpr int SM_LIST  = SM_XOWN + 80 * 128;
constexpr int SM_STAGE = SM_LIST;
constexpr int NULLT    = NPB * LIST_LD;
constexpr int SM_T     = SM_LIST + NULLT - 80 * T_LD;
constexpr int SM_W     = (SM_LIST + NULLT + 128 + 1023) / 1024 * 1024;
constexpr int W_BYTES  = (4 * 64 + 16) * 128;
constexpr int SM_IEA   = SM_W;
constexpr int SM_PART  = SM_W + 16384;
constexpr int SM_U     = SM_W + W_BYTES;
constexpr int SM_WCF   = SM_U + 80 * U_LD;
constexpr int SM_CNT   = SM_WCF + 2048;
constexpr int SM_NCNT  = SM_CNT + 2 * 136 * 4;
constexpr int SM_MISC  = SM_NCNT + 80 * 4;
constexpr int SM_STATE = SM_MISC + 8 * 4;
constexpr int SM_DCNT  = SM_STATE + 32 * 4;
constexpr int SM_DUMP  = SM_DCNT + 32 * 4;
constexpr int SM_TOTAL = SM_DUMP + 32 * 8;
static_assert(SM_STAGE + NB * SEG_LD * 4 <= SM_T && SM_T % 16 == 0, "staging fits");
static_assert(SM_W % 16 == 0 && NULLT % 16 == 0, "alignment");
constexpr uint32_t REC_NONE = 0x7F000000u, REC_OVF = 0x7E000000u;
static_assert((unsigned long long)CHUNK / 2 * NPB * N_NODES <= REC_OVF, "record fits 31 bits");
static_assert(80 * U_LD <= 16384 && NSPLIT <= 32, "aliases fit");
static_assert(SM_TOTAL <= 134144, "fits the 132 KB carve-out");

constexpr int WS_B = 0, WS_V = 8192, WS_A = 16384, WS_U = 24576, WS_C = 32768;

constexpr uint32_t NULL_MIN = (uint32_t)N_NODES * 256u;
constexpr float L2E = 1.4426950408889634f;
constexpr float RSCALE = 17.906f;
constexpr float USHIFT = 11.0f, RANGE_AB = 72.0f, RANGE_A = 50.0f;

__device__ __align__(128) unsigned int g_epoch[NB * 8];
__device__ __align__(128) unsigned long long g_flag[NB];
__device__ __align__(128) uint4 g_seg[(size_t)4 * NB * NB * UMAIN];
__device__ __align__(256) uint4 g_tab[(size_t)(N_NODES + NB) * 16];
__device__ float2 g_acc[(size_t)NB * NPB * 64];


__device__ __forceinline__ void cp_async16(uint32_t dst, const void* src) {
    asm volatile("cp.async.cg.shared.global [%0], [%1], 16;" :: "r"(dst), "l"(src) : "memory");
}
__device__ __forceinline__ void cp_async16_zfill(uint32_t dst, const void* src, int sz) {
    asm volatile("cp.async.cg.shared.global [%0], [%1], 16, %2;" :: "r"(dst), "l"(src), "r"(sz) : "memory");
}
__device__ __forceinline__ void cp_commit() { asm volatile("cp.async.commit_group;" ::: "memory"); }
template <int N> __device__ __forceinline__ void cp_wait() { asm volatile("cp.async.wait_group %0;" :: "n"(N) : "memory"); }
__device__ __forceinline__ void fence_async() { asm volatile("fence.proxy.async.shared::cta;" ::: "memory"); }
__device__ __forceinline__ void wgmma_fence() { asm volatile("wgmma.fence.sync.aligned;" ::: "memory"); }
__device__ __forceinline__ void wgmma_commit() { asm volatile("wgmma.commit_group.sync.aligned;" ::: "memory"); }
template <int N> __device__ __forceinline__ void wgmma_wait() { asm volatile("wgmma.wait_group.sync.aligned %0;" :: "n"(N) : "memory"); }
__device__ __forceinline__ void bar_sync(int id, int n) { asm volatile("bar.sync %0, %1;" :: "r"(id), "r"(n) : "memory"); }
__device__ __forceinline__ void bar_arrive(int id, int n) { asm volatile("bar.arrive %0, %1;" :: "r"(id), "r"(n) : "memory"); }
__device__ __forceinline__ int uni(int v) { return __shfl_sync(0xffffffffu, v, 0); }

__device__ __forceinline__ void ldsm_x4_t(uint32_t (&r)[4], uint32_t addr) {
    asm volatile("ldmatrix.sync.aligned.m8n8.x4.trans.shared.b16 {%0,%1,%2,%3}, [%4];"
                 : "=r"(r[0]), "=r"(r[1]), "=r"(r[2]), "=r"(r[3]) : "r"(addr) : "memory");
}
__device__ __forceinline__ void stsm_x4_t(uint32_t addr, uint32_t r0, uint32_t r1, uint32_t r2, uint32_t r3) {
    asm volatile("stmatrix.sync.aligned.m8n8.x4.trans.shared.b16 [%0], {%1,%2,%3,%4};"
                 :: "r"(addr), "r"(r0), "r"(r1), "r"(r2), "r"(r3) : "memory");
}
__device__ __forceinline__ uint32_t movm(uint32_t a) {
    uint32_t d; asm volatile("movmatrix.sync.aligned.m8n8.trans.b16 %0, %1;" : "=r"(d) : "r"(a)); return d;
}
__device__ __forceinline__ uint32_t lds32(uint32_t addr) {
    uint32_t v; asm volatile("ld.shared.u32 %0, [%1];" : "=r"(v) : "r"(addr) : "memory"); return v;
}
__device__ __forceinline__ uint2 lds64(uint32_t addr) {
    uint2 v; asm volatile("ld.shared.v2.u32 {%0,%1}, [%2];" : "=r"(v.x), "=r"(v.y) : "r"(addr) : "memory"); return v;
}
__device__ __forceinline__ uint4 lds128(uint32_t addr) {
    uint4 v; asm volatile("ld.shared.v4.u32 {%0,%1,%2,%3}, [%4];" : "=r"(v.x), "=r"(v.y), "=r"(v.z), "=r"(v.w) : "r"(addr) : "memory"); return v;
}
__device__ __forceinline__ void sts64(uint32_t addr, uint32_t a, uint32_t b) {
    asm volatile("st.shared.v2.u32 [%0], {%1,%2};" :: "r"(addr), "r"(a), "r"(b) : "memory");
}
__device__ __forceinline__ void sts128(uint32_t addr, uint32_t a, uint32_t b, uint32_t c, uint32_t d) {
    asm volatile("st.shared.v4.u32 [%0], {%1,%2,%3,%4};" :: "r"(addr), "r"(a), "r"(b), "r"(c), "r"(d) : "memory");
}
__device__ __forceinline__ void ldg128(uint32_t* r, const char* p) {
    asm volatile("ld.global.v4.u32 {%0,%1,%2,%3}, [%4];" : "=r"(r[0]), "=r"(r[1]), "=r"(r[2]), "=r"(r[3]) : "l"(p) : "memory");
}
__device__ __forceinline__ void ldg64_stream_if(uint32_t& a, uint32_t& b, const char* p, bool v) {
    asm volatile("{\n\t.reg .pred p;\n\tsetp.ne.u32 p, %3, 0;\n\t@p ld.global.nc.L1::no_allocate.v2.u32 {%0,%1}, [%2];\n\t}"
                 : "+r"(a), "+r"(b) : "l"(p), "r"((uint32_t)v) : "memory");
}
__device__ __forceinline__ int4 ldg_stream(const int4* p) {
    int4 v;
    asm volatile("ld.volatile.global.v4.s32 {%0,%1,%2,%3}, [%4];" : "=r"(v.x), "=r"(v.y), "=r"(v.z), "=r"(v.w) : "l"(p) : "memory");
    return v;
}

__device__ __forceinline__ void mma_k16(float* d, uint32_t a0, uint32_t a1, uint32_t a2, uint32_t a3, uint32_t b0, uint32_t b1,
                                        float c0, float c1, float c2, float c3) {
    asm volatile("mma.sync.aligned.m16n8k16.row.col.f32.bf16.bf16.f32 {%0,%1,%2,%3}, {%4,%5,%6,%7}, {%8,%9}, {%10,%11,%12,%13};"
                 : "=f"(d[0]), "=f"(d[1]), "=f"(d[2]), "=f"(d[3])
                 : "r"(a0), "r"(a1), "r"(a2), "r"(a3), "r"(b0), "r"(b1), "f"(c0), "f"(c1), "f"(c2), "f"(c3));
}
__device__ __forceinline__ uint64_t desc_sw128(uint32_t saddr) {
    return (uint64_t)((saddr & 0x3FFFF) >> 4) | (1ull << 16) | (64ull << 32) | (1ull << 62);
}
template <int SCALE_D>
__device__ __forceinline__ void wgmma_n80(float (&d)[40], uint64_t da, uint64_t db) {
    asm volatile(
        "wgmma.mma_async.sync.aligned.m64n80k16.f32.bf16.bf16 "
        "{%0,%1,%2,%3,%4,%5,%6,%7,%8,%9,%10,%11,%12,%13,%14,%15,"
        "%16,%17,%18,%19,%20,%21,%22,%23,%24,%25,%26,%27,%28,%29,%30,%31,"
        "%32,%33,%34,%35,%36,%37,%38,%39}, "
        "%40, %41, %42, 1, 1, 1, 0;"
        : "+f"(d[0]), "+f"(d[1]), "+f"(d[2]), "+f"(d[3]), "+f"(d[4]), "+f"(d[5]), "+f"(d[6]), "+f"(d[7]),
          "+f"(d[8]), "+f"(d[9]), "+f"(d[10]), "+f"(d[11]), "+f"(d[12]), "+f"(d[13]), "+f"(d[14]), "+f"(d[15]),
          "+f"(d[16]), "+f"(d[17]), "+f"(d[18]), "+f"(d[19]), "+f"(d[20]), "+f"(d[21]), "+f"(d[22]), "+f"(d[23]),
          "+f"(d[24]), "+f"(d[25]), "+f"(d[26]), "+f"(d[27]), "+f"(d[28]), "+f"(d[29]), "+f"(d[30]), "+f"(d[31]),
          "+f"(d[32]), "+f"(d[33]), "+f"(d[34]), "+f"(d[35]), "+f"(d[36]), "+f"(d[37]), "+f"(d[38]), "+f"(d[39])
        : "l"(da), "l"(db), "n"(SCALE_D));
}
__device__ __forceinline__ void node_gemm(float (&d)[40], uint32_t wa, uint32_t xa) {
    const uint64_t da = desc_sw128(wa), db = desc_sw128(xa);
    wgmma_n80<0>(d, da, db);
    wgmma_n80<1>(d, da + 128, db + 2);
    wgmma_n80<1>(d, da + 256, db + 4);
    wgmma_n80<1>(d, da + 384, db + 6);
}
template <int NREG>
__device__ __forceinline__ void reg_fence(float (&d)[NREG]) {
    #pragma unroll
    for (int i = 0; i < NREG; i++) asm volatile("" : "+f"(d[i]) :: "memory");
}

__device__ __forceinline__ uint32_t pack_bf16(float lo, float hi) {
    uint32_t d; asm("cvt.rn.bf16x2.f32 %0, %1, %2;" : "=r"(d) : "f"(hi), "f"(lo)); return d;
}
__device__ __forceinline__ uint32_t fma_bf2(uint32_t a, uint32_t b, uint32_t c) {
    uint32_t d; asm("fma.rn.bf16x2 %0, %1, %2, %3;" : "=r"(d) : "r"(a), "r"(b), "r"(c)); return d;
}
__device__ __forceinline__ uint32_t add_bf2(uint32_t a, uint32_t b) {
    uint32_t d; asm("add.rn.bf16x2 %0, %1, %2;" : "=r"(d) : "r"(a), "r"(b)); return d;
}
__device__ __forceinline__ float ex2f(float x) {
    float y; asm("ex2.approx.ftz.f32 %0, %1;" : "=f"(y) : "f"(x)); return y;
}
__device__ __forceinline__ float rcpf(float x) {
    float y; asm("rcp.approx.ftz.f32 %0, %1;" : "=f"(y) : "f"(x)); return y;
}
__device__ __forceinline__ uint32_t fma_relu_bf2(uint32_t a, uint32_t b, uint32_t c) {
    uint32_t d; asm("fma.rn.relu.bf16x2 %0, %1, %2, %3;" : "=r"(d) : "r"(a), "r"(b), "r"(c)); return d;
}
__device__ __forceinline__ uint32_t gate_pair(float y0, float y1, uint32_t neb, uint32_t niea) {
    const uint32_t na = fma_bf2(pack_bf16(ex2f(y0), ex2f(y1)), neb, niea);
    const uint32_t r0 = ~na;
    const uint32_t e  = fma_relu_bf2(na, r0, 0x40EF40EFu);
    return fma_bf2(r0, e, r0);
}

__device__ __forceinline__ uint4 ld_relaxed_128(const uint4* p) {
    unsigned __int128 t;
    asm volatile("ld.relaxed.gpu.global.b128 %0, [%1];" : "=q"(t) : "l"(p) : "memory");
    return make_uint4((uint32_t)t, (uint32_t)(t >> 32), (uint32_t)(t >> 64), (uint32_t)(t >> 96));
}
__device__ __forceinline__ void st_relaxed_128(uint4* p, uint4 v) {
    const unsigned __int128 t = (unsigned __int128)(((uint64_t)v.w << 32) | v.z) << 64 | (((uint64_t)v.y << 32) | v.x);
    asm volatile("st.relaxed.gpu.global.b128 [%0], %1;" :: "l"(p), "q"(t) : "memory");
}
__device__ __forceinline__ void sts32(uint32_t addr, uint32_t a) { asm volatile("st.shared.u32 [%0], %1;" :: "r"(addr), "r"(a) : "memory"); }
__device__ __forceinline__ uint32_t atoms_inc_if(uint32_t addr, bool p, uint32_t dflt) {
    uint32_t r = dflt;
    asm volatile("{\n\t.reg .pred p;\n\tsetp.ne.u32 p, %2, 0;\n\t@p atom.shared.inc.u32 %0, [%1], 0x7FFFFFFF;\n\t}"
                 : "+r"(r) : "r"(addr), "r"((uint32_t)p) : "memory");
    return r;
}
__device__ __forceinline__ uint32_t atoms_inc(uint32_t addr) {
    uint32_t r; asm volatile("atom.shared.add.u32 %0, [%1], 1;" : "=r"(r) : "r"(addr) : "memory"); return r;
}

__global__ void __launch_bounds__(NTHREADS, 1)
gatedgcn_kernel(const __nv_bfloat16* __restrict__ x, const __nv_bfloat16* __restrict__ e_attr,
                const int* __restrict__ src, const int* __restrict__ dst,
                const __nv_bfloat16* __restrict__ w_a, const __nv_bfloat16* __restrict__ w_b,
                const __nv_bfloat16* __restrict__ w_c, const __nv_bfloat16* __restrict__ w_u,
                const __nv_bfloat16* __restrict__ w_v, __nv_bfloat16* __restrict__ out) {
    extern __shared__ __align__(1024) unsigned char smem[];
    const uint32_t sb = (uint32_t)__cvta_generic_to_shared(smem);
    const int tid = threadIdx.x, lane = tid & 31;
    const int warp = uni(tid >> 5);
    const int cta = blockIdx.x;
    const int node0 = cta * NPB;
    const int g = lane >> 2, q = lane & 3;
    const uint32_t NULL_W0 = NULL_MIN + cta * 256u;

    int* s_cnt  = (int*)(smem + SM_CNT);
    int* s_ncnt = (int*)(smem + SM_NCNT);
    volatile int* s_misc = (volatile int*)(smem + SM_MISC);

    auto load_weights = [&](int t, int nt) {
        #pragma unroll 1
        for (int i = t; i < 512; i += nt) {
            const uint32_t so = sb + SM_W + (i >> 3) * 128 + (((i ^ (i >> 3)) & 7) << 4);
            cp_async16(so + WS_B, w_b + i * 8);
            cp_async16(so + WS_V, w_v + i * 8);
            cp_async16(so + WS_A, w_a + i * 8);
            cp_async16(so + WS_U, w_u + i * 8);
        }
        if (t < 128) cp_async16(sb + SM_W + WS_C + (t >> 3) * 128 + (((t ^ (t >> 3)) & 7) << 4), w_c + t * 8);
    };

    auto store_rows = [&](const float (&d)[40], uint32_t base, int ld) {
        base += ((lane & 7) + ((lane >> 4) << 3)) * ld + ((warp & 3) * 16 + ((lane >> 3) & 1) * 8) * 2;
        #pragma unroll
        for (int w = 0; w < 10; w += 2)
            stsm_x4_t(base + w * 8 * ld,
                      pack_bf16(d[4 * w + 0], d[4 * w + 1]), pack_bf16(d[4 * w + 2], d[4 * w + 3]),
                      pack_bf16(d[4 * w + 4], d[4 * w + 5]), pack_bf16(d[4 * w + 6], d[4 * w + 7]));
    };
    auto neg_exp = [&](float (&d)[40], float scale, float bias, int slot) {
        float mx = 0.f;
        #pragma unroll
        for (int i = 0; i < 40; i++) { mx = fmaxf(mx, fabsf(d[i])); d[i] = -ex2f(fmaf(d[i], scale, bias)); }
        const uint32_t mb = __reduce_max_sync(0xffffffffu, __float_as_uint(mx));
        if (lane == 0) atomicMax((unsigned int*)&s_misc[slot], mb);
    };
    if (warp < NET / 32) {
        const int ebase = cta * CHUNK;
        const int nvec = (min(CHUNK, N_EDGES - ebase)) >> 2;
        const int sg = tid / UMAIN, su = tid - sg * UMAIN;
        const bool act_last = sg + (UPT - 1) * SPP < NB;
        int4 dv[4], sv[4];
        bool has[4];
        #pragma unroll
        for (int k = 0; k < 4; k++) {
            const int o = tid + (k & 1) * NET, v = (k >> 1) * WVEC + o;
            has[k] = o < WVEC && v < nvec;
            if (k == 2) {
                if (tid < 272 + 80 + 4 && tid != 272 + 80) s_cnt[tid] = 0;
                bar_sync(1, NET);
            }
            if (k >= 2) has[k] = has[k] && (dv[0].x | sv[0].x | (has[1] ? dv[1].x | sv[1].x : 0)) >= 0;
            if (has[k]) {
                dv[k] = ldg_stream((const int4*)(dst + ebase) + v);
                sv[k] = ldg_stream((const int4*)(src + ebase) + v);
            }
        }
        uint32_t tag = 0;
        #pragma unroll
        for (int w = 0; w < 2; w++) {
            if (w == 1) bar_sync(1, NET);
            #pragma unroll
            for (int k = 2 * w; k < 2 * w + 2; k++) {
                if (has[k]) {
                    const int v = tid + (k & 1) * NET;
                    const int dd[4] = {dv[k].x, dv[k].y, dv[k].z, dv[k].w};
                    const int ss[4] = {sv[k].x, sv[k].y, sv[k].z, sv[k].w};
                    uint32_t b[4], rank[4];
                    #pragma unroll
                    for (int j = 0; j < 4; j++) { b[j] = (uint32_t)dd[j] / NPB; rank[j] = (uint32_t)atomicAdd(&s_cnt[w * 136 + b[j]], 1); }
                    #pragma unroll
                    for (int j = 0; j < 4; j++) {
                        const uint32_t rec = (((uint32_t)(v * 4 + j) - b[j]) * NPB + (uint32_t)dd[j]) * N_NODES + (uint32_t)ss[j];
                        sts32(sb + SM_STAGE + (b[j] * SEG_LD + min(rank[j], (uint32_t)SEGCAP)) * 4, rec);
                    }
                }
            }
            if (w == 0) { bar_sync(8, NET + 32); tag = ((uint32_t)s_misc[0] + 1u) & 0xFFFFFFu; }
            else bar_sync(1, NET);
            {
                const uint32_t a = sb + SM_STAGE + (sg * SEG_LD + 4 * su) * 4;
                uint4* gq = g_seg + (size_t)w * 2 * TAIL + ((size_t)sg * NB + cta) * UMAIN + su;
                uint32_t tmask = 0;
                uint4 pu[UPT];
                #pragma unroll
                for (int k = 0; k < UPT; k++) {
                    const bool on = k < UPT - 1 || act_last;
                    const int cnt = on ? s_cnt[w * 136 + sg + k * SPP] : 0, n = cnt - 4 * su;
                    const uint4 v = lds128(on ? a + k * SPP * SEG_LD * 4 : a);
                    pu[k].x = (n > 0 ? v.x : REC_NONE) | tag << 31;
                    pu[k].y = (n > 1 ? v.y : REC_NONE) | (tag >> 1) << 31;
                    pu[k].z = (n > 2 ? v.z : REC_NONE) | (tag >> 2) << 31;
                    pu[k].w = cnt > SEGCAP ? REC_OVF : (n > 3 ? v.w : REC_NONE) | (cnt > 4 * UMAIN + 3 * su ? 0x80000000u : 0u);
                    if (cnt > 4 * UMAIN + 3 * (su & ~1) && cnt <= SEGCAP) tmask |= 1u << k;
                }
                #pragma unroll
                for (int k = 0; k < UPT; k++)
                    if (k < UPT - 1 || act_last) st_relaxed_128(gq + (size_t)k * SPP * NB * UMAIN, pu[k]);
                while (tmask) {
                    const int k = __ffs(tmask) - 1;
                    tmask &= tmask - 1;
                    const uint32_t ta = a + (k * SPP * SEG_LD + 4 * UMAIN - su) * 4;
                    const int n = s_cnt[w * 136 + sg + k * SPP] - 4 * UMAIN - 3 * su;
                    st_relaxed_128(gq + (size_t)k * SPP * NB * UMAIN + TAIL,
                                   make_uint4(n > 0 ? lds32(ta) : REC_NONE, n > 1 ? lds32(ta + 4) : REC_NONE, n > 2 ? lds32(ta + 8) : REC_NONE, REC_NONE | tag));
                }
            }
        }
        const uint4* gp = g_seg + (size_t)cta * NB * UMAIN + tid;
        const uint32_t dcnt = sb + SM_DCNT + lane * 4, dump = sb + SM_DUMP + lane * 8 - CAPN * 8;
        const uint4 none = make_uint4(REC_NONE | tag << 31, REC_NONE | (tag >> 1) << 31, REC_NONE | (tag >> 2) << 31, REC_NONE | tag);
        uint4 rec[2 * UPT];
        auto fetch = [&](int w) {
            #pragma unroll
            for (int k = 0; k < UPT; k++) {
                rec[w * UPT + k] = none;
                if (k < UPT - 1 || act_last) rec[w * UPT + k] = ld_relaxed_128(gp + w * 2 * TAIL + k * SPP * UMAIN);
            }
        };
        fetch(0);
        bar_sync(3, NTHREADS);
        bool first = true;
        uint32_t todo = 3;
        #pragma unroll 1
        while (todo) {
            #pragma unroll
            for (int w = 0; w < 2; w++) {
                if (!(todo >> w & 1)) continue;
                bool more = false;
                for (int tries = 0;; tries++) {
                    bool ok = true;
                    #pragma unroll
                    for (int k = 0; k < UPT; k++) {
                        uint4& u = rec[w * UPT + k];
                        const bool stale = first ? (int)((u.x ^ none.x) | (u.y ^ none.y) | (u.z ^ none.z)) < 0 : u.w != none.w;
                        if (stale) { u = ld_relaxed_128(gp + w * 2 * TAIL + k * SPP * UMAIN); ok = false; }
                    }
                    if (__all_sync(0xffffffffu, ok)) break;
                    if (tries > 400000) {
                        s_misc[1] = 1;
                        #pragma unroll
                        for (int k = 0; k < UPT; k++) rec[w * UPT + k] = none;
                    }
                }
                uint32_t sv_[UPT][4], el[UPT][4], la[UPT][4], r[UPT][4];
                #pragma unroll
                for (int k = 0; k < UPT; k++) {
                    uint4& u = rec[w * UPT + k];
                    const uint32_t rw[4] = {u.x & 0x7FFFFFFFu, u.y & 0x7FFFFFFFu, u.z & 0x7FFFFFFFu, u.w & 0x7FFFFFFFu};
                    #pragma unroll
                    for (int j = 0; j < 4; j++) {
                        const uint32_t t = rw[j] / N_NODES;
                        el[k][j] = t / NPB;
                        const uint32_t dl = t - el[k][j] * NPB;
                        sv_[k][j] = (rw[j] - t * N_NODES) << 8;
                        const bool valid = rw[j] < REC_OVF;
                        la[k][j] = valid ? sb + SM_LIST + dl * LIST_LD : dump;
                        r[k][j] = atoms_inc(valid ? sb + SM_NCNT + dl * 4 : dcnt);
                    }
                    if (u.w == REC_OVF) s_misc[1] = 1;
                    const bool tl = (int)u.w < 0;
                    u = none;
                    if (tl) { u = ld_relaxed_128(gp + w * 2 * TAIL + k * SPP * UMAIN + TAIL); more = true; }
                }
                if (!__any_sync(0xffffffffu, more)) todo &= ~(1u << w);
                #pragma unroll
                for (int k = 0; k < UPT; k++)
                    #pragma unroll
                    for (int j = 0; j < 4; j++)
                        sts64(la[k][j] + min(r[k][j], (uint32_t)CAPN) * 8, sv_[k][j], ((sg + k * SPP) * CHUNK + w * (CHUNK / 2) + el[k][j]) * 32u);
                if (w == 0 && first) fetch(1);
            }
            first = false;
            gp += TAIL;
        }
    } else {
        const int wtid = tid - NET;
        uint32_t epoch = 0;
        if (wtid == 96) epoch = *(volatile unsigned int*)&g_epoch[cta * 8];
        {
            const uint32_t so = (wtid >> 3) * 128 + (((wtid ^ (wtid >> 3)) & 7) << 4);
            #pragma unroll
            for (int k = 0; k < 5; k++) {
                const int r = (wtid >> 3) + 16 * k;
                const bool ok = r < NPB && node0 + r < N_NODES;
                cp_async16_zfill(sb + SM_XOWN + so + k * 2048, x + (ok ? (size_t)node0 * 64 + wtid * 8 + k * 1024 : 0), ok ? 16 : 0);
            }
            #pragma unroll
            for (int k = 0; k < 4; k++) {
                cp_async16(sb + SM_W + WS_V + so + k * 2048, w_v + wtid * 8 + k * 1024);
                cp_async16(sb + SM_W + WS_B + so + k * 2048, w_b + wtid * 8 + k * 1024);
            }
            cp_commit();
            #pragma unroll
            for (int k = 0; k < 4; k++) {
                cp_async16(sb + SM_W + WS_A + so + k * 2048, w_a + wtid * 8 + k * 1024);
                cp_async16(sb + SM_W + WS_U + so + k * 2048, w_u + wtid * 8 + k * 1024);
            }
            cp_async16(sb + SM_W + WS_C + so, w_c + wtid * 8);
            cp_commit();
        }
        if (wtid >= 96) {
            if (lane == 0) { s_misc[0] = (int)epoch; g_epoch[cta * 8] = epoch + 1u; }
            __syncwarp();
            bar_arrive(8, NET + 32);
        }
        if (wtid < 8) sts128(sb + SM_LIST + NULLT + wtid * 16, NULL_W0, 0u, NULL_W0, 0u);
        if (wtid >= 8 && wtid < 12) s_misc[wtid - 4] = 0;
        if (wtid >= 32 && wtid < 96) s_misc[wtid - 24] = wtid < 64 ? 0 : CAPN;
        cp_wait<1>();
        fence_async();
        bar_sync(2, 128);
        {
            float db[40], dv[40];
            wgmma_fence();
            node_gemm(dv, sb + SM_W + WS_V, sb + SM_XOWN);
            wgmma_commit();
            node_gemm(db, sb + SM_W + WS_B, sb + SM_XOWN);
            wgmma_commit();
            wgmma_wait<1>();
            reg_fence(dv);
            store_rows(dv, sb + SM_T + 128, T_LD);
            float mv = 0.f;
            #pragma unroll
            for (int i = 0; i < 40; i++) mv = fmaxf(mv, fabsf(dv[i]));
            if (mv > 1e9f) s_misc[5] = 0x7F800000;
            wgmma_wait<0>();
            reg_fence(db);
            neg_exp(db, -L2E, 0.f, 5);
            store_rows(db, sb + SM_T, T_LD);
        }
        bar_sync(2, 128);
        {
            uint4 v[10];
            #pragma unroll
            for (int k = 0; k < 10; k++)
                v[k] = lds128(sb + SM_T + ((wtid >> 4) + 8 * k) * T_LD + (wtid & 1) * 128 + ((wtid >> 1) & 7) * 16);
            #pragma unroll
            for (int k = 0; k < 10; k++) {
                const int r = (wtid >> 4) + 8 * k;
                if (r < NPB && node0 + r < N_NODES) g_tab[(size_t)node0 * 16 + wtid + k * 128] = v[k];
            }
            const uint32_t nv = (wtid & 1) ? 0u : 0xFF80FF80u;
            if (wtid < 16) g_tab[(size_t)(N_NODES + cta) * 16 + wtid] = make_uint4(nv, nv, nv, nv);
        }
        cp_wait<0>();
        fence_async();
        bar_arrive(3, NTHREADS);
        bar_sync(2, 128);
        const uint32_t ftag = (uint32_t)s_misc[0] + 1u;
        {
            float da[40], du[40];
            wgmma_fence();
            node_gemm(du, sb + SM_W + WS_U, sb + SM_XOWN);
            node_gemm(da, sb + SM_W + WS_A, sb + SM_XOWN);
            wgmma_commit();
            if (wtid == 96)
                asm volatile("st.release.gpu.global.u64 [%0], %1;"
                             :: "l"(&g_flag[cta]), "l"(((unsigned long long)ftag << 32) | (uint32_t)s_misc[5]) : "memory");
            __syncwarp();
            wgmma_wait<0>();
            reg_fence(du);
            reg_fence(da);
            store_rows(du, sb + SM_U, U_LD);
            neg_exp(da, L2E, -USHIFT, 4);
            store_rows(da, sb + SM_IEA, U_LD);
        }
        if (wtid < 96) {
            #pragma unroll 2
            for (int i = wtid; i < 512; i += 96) {
                const int l = i >> 4, j = (i >> 1) & 7, h = i & 1;
                const int f = 32 * (j >> 2) + 8 * (l >> 3) + 2 * (j & 3) + ((l >> 2) & 1);
                const int r = 4 * (l & 3) + 2 * h;
                const unsigned char* wc = smem + SM_W + WS_C + (f & 7) * 2;
                const float c0 = __bfloat162float(*(const __nv_bfloat16*)(wc + r * 128 + (((f >> 3) ^ (r & 7)) << 4)));
                const float c1 = __bfloat162float(*(const __nv_bfloat16*)(wc + (r + 1) * 128 + (((f >> 3) ^ ((r + 1) & 7)) << 4)));
                ((uint32_t*)(smem + SM_WCF))[((i >> 2) & 3) * 128 + l * 4 + (i & 3)] = pack_bf16(c0 * -L2E, c1 * -L2E);
            }
            unsigned long long f0 = (unsigned long long)ftag << 32, f1 = f0;
            for (int tries = 0;; tries++) {
                if (wtid < NB / 2)
                    asm volatile("ld.acquire.gpu.global.v2.u64 {%0,%1}, [%2];" : "=l"(f0), "=l"(f1) : "l"(g_flag + 2 * wtid) : "memory");
                if (__all_sync(0xffffffffu, (uint32_t)(f0 >> 32) == ftag && (uint32_t)(f1 >> 32) == ftag)) break;
                if (tries > 100000) { f0 = 0x7F800000u; break; }
            }
            const uint32_t mx = __reduce_max_sync(0xffffffffu, max((uint32_t)f0, (uint32_t)f1));
            if (lane == 0) atomicMax((unsigned int*)&s_misc[6], mx);
        }
    }
    __syncthreads();
    const bool bad_list = s_misc[1] != 0 ||
        __any_sync(0xffffffffu, max(max(s_ncnt[lane], s_ncnt[lane + 32]), s_ncnt[min(lane + 64, NPB - 1)]) > CAPN);

    auto reduce_rows = [&](float (&sum)[4], const uint32_t (&den)[8], const uint32_t (&num)[8]) {
        float s1[4] = {0.f, 0.f, 0.f, 0.f}, s2[4] = {0.f, 0.f, 0.f, 0.f};
        uint32_t ln;
        asm volatile("mov.u32 %0, %%laneid;" : "=r"(ln));
        #pragma unroll
        for (int j = 0; j < 4; j++) {
            const uint32_t sel = ((ln >> 2) & 3) == j ? 0x3F803F80u : 0u;
            mma_k16(s1, sel, 0u, 0u, sel, movm(den[j]), movm(num[j]), s1[0], s1[1], s1[2], s1[3]);
            mma_k16(s2, sel, 0u, 0u, sel, movm(den[j + 4]), movm(num[j + 4]), s2[0], s2[1], s2[2], s2[3]);
        }
        #pragma unroll
        for (int i = 0; i < 4; i++) sum[i] = ln < 16 ? s1[i] : s2[i];
    };
    auto write_node = [&](int node, const float (&sum)[4], int f0) {
        if (node0 + node < N_NODES) {
            const uint32_t iw = lds32(sb + SM_IEA + node * U_LD + f0 * 2);
            const uint32_t uw = lds32(sb + SM_U + node * U_LD + f0 * 2);
            const uint32_t xw = lds32(sb + SM_XOWN + node * 128 + (((f0 >> 3) ^ (node & 7)) << 4) + (f0 & 7) * 2);
            const float i0 = __uint_as_float(iw << 16), i1 = __uint_as_float(iw & 0xFFFF0000u);
            const float z0 = __uint_as_float(uw << 16) + sum[2] * i0 * rcpf(fmaf(sum[0], i0, -RSCALE * 1e-6f));
            const float z1 = __uint_as_float(uw & 0xFFFF0000u) + sum[3] * i1 * rcpf(fmaf(sum[1], i1, -RSCALE * 1e-6f));
            const float o0 = __uint_as_float(xw << 16) + fmaxf(z0, 0.f);
            const float o1 = __uint_as_float(xw & 0xFFFF0000u) + fmaxf(z1, 0.f);
            *(uint32_t*)(out + (size_t)(node0 + node) * 64 + f0) = pack_bf16(o0, o1);
        }
    };
    const char* eq = (const char*)e_attr + q * 8;
    const uint32_t la = sb + SM_LIST + g * 8;
    const bool fast = !bad_list && __int_as_float(s_misc[4]) <= RANGE_A && __int_as_float(s_misc[4]) + __int_as_float(s_misc[6]) <= RANGE_AB;

    if (fast) {
        auto job_range = [&](int j, int& tb, int& te) {
            tb = NULLT; te = NULLT + 128;
            if (j >= NJOBS) return -1;
            const int n = j < NWHOLE ? j : NWHOLE + ((j - NWHOLE) >> 1);
            const int cnt = s_ncnt[n];
            const int nt = max(1, (cnt + 15) >> 4);
            if (cnt + lane < nt * 16) sts64(sb + SM_LIST + n * LIST_LD + (cnt + lane) * 8, NULL_W0, 0u);
            __syncwarp();
            const int mid = j < NWHOLE ? nt : (nt + 1) >> 1;
            const bool second = j >= NWHOLE && ((j - NWHOLE) & 1);
            if (!second) { tb = n * LIST_LD; te = tb + mid * 128; }
            else if (mid < nt) { tb = n * LIST_LD + mid * 128; te = n * LIST_LD + nt * 128; }
            return n;
        };
        const char* tabq = (const char*)g_tab + q * 32;
        asm volatile("" : "+l"(tabq));
        uint32_t wcf[16];
        #pragma unroll
        for (int i = 0; i < 4; i++) {
            const uint4 v = lds128(sb + SM_WCF + i * 512 + lane * 16);
            wcf[4 * i] = v.x; wcf[4 * i + 1] = v.y; wcf[4 * i + 2] = v.z; wcf[4 * i + 3] = v.w;
        }
        uint32_t eb[2][8], hq[2][8], ev[4] = {0u, 0u, 0u, 0u};
        const char *p0, *p1;
        bool v0, v1;
        auto load_rec = [&](int tt) {
            const uint2 r0 = lds64(la + tt), r1 = lds64(la + tt + 64);
            p0 = tabq + r0.x; p1 = tabq + r1.x;
            v0 = r0.x < NULL_MIN; v1 = r1.x < NULL_MIN;
            ldg64_stream_if(ev[0], ev[2], eq + r0.y, v0);
            ldg64_stream_if(ev[1], ev[3], eq + r1.y, v1);
        };
        auto load_half = [&](int h) {
            ldg128(&eb[0][4 * h], p0 + 128 * h); ldg128(&eb[1][4 * h], p1 + 128 * h);
            ldg128(&hq[0][4 * h], p0 + 16 + 128 * h); ldg128(&hq[1][4 * h], p1 + 16 + 128 * h);
        };
        auto load_rows = [&]() { load_half(0); load_half(1); };
        const int yes = s_misc[1] == 0;
        int t, te;
        int node = job_range(warp, t, te);
        load_rec(t);
        load_rows();
        while (true) {
            int nnode = 0;
            uint32_t iea[8], den[8], num[8];
            {
                const uint4 w0 = lds128(sb + SM_IEA + node * U_LD + q * 16), w1 = lds128(sb + SM_IEA + node * U_LD + 64 + q * 16);
                iea[0] = w0.x; iea[1] = w0.y; iea[2] = w0.z; iea[3] = w0.w; iea[4] = w1.x; iea[5] = w1.y; iea[6] = w1.z; iea[7] = w1.w;
            }
            #pragma unroll
            for (int j = 0; j < 8; j++) { den[j] = 0u; num[j] = 0u; }
            bool last;
            do {
                const uint32_t a0 = v0 ? ev[0] : 0u, a1 = v1 ? ev[1] : 0u, a2 = v0 ? ev[2] : 0u, a3 = v1 ? ev[3] : 0u;
                const bool upper = __any_sync(0xffffffffu, v1);
                t += 128;
                last = t == te;
                if (last) nnode = job_range(uni((int)atoms_inc_if(sb + SM_MISC + 12, lane == 0, 0u)) + NWARPS, t, te);
                load_rec(t);
                if (upper) {
                    #pragma unroll
                    for (int h = 0; h < 2; h++) {
                        if (h == 1) { int y = yes; asm volatile("" : "+r"(y) :: "memory"); if (!y) break; }
                        float d[16];
                        #pragma unroll
                        for (int j = 0; j < 4; j++)
                            mma_k16(&d[4 * j], a0, a1, a2, a3, wcf[8 * h + 2 * j], wcf[8 * h + 2 * j + 1], -USHIFT, -USHIFT, -USHIFT, -USHIFT);
                        #pragma unroll
                        for (int jj = 0; jj < 4; jj++) {
                            const int j = 4 * h + jj;
                            const uint32_t ra = gate_pair(d[4 * jj], d[4 * jj + 1], eb[0][j], iea[j]);
                            const uint32_t rb = gate_pair(d[4 * jj + 2], d[4 * jj + 3], eb[1][j], iea[j]);
                            den[j] = add_bf2(add_bf2(den[j], ra), rb);
                            num[j] = fma_bf2(rb, hq[1][j], fma_bf2(ra, hq[0][j], num[j]));
                        }
                        load_half(h);
                    }
                } else {
                    #pragma unroll
                    for (int j = 0; j < 8; j++) {
                        float d[4];
                        mma_k16(d, a0, a1, a2, a3, wcf[2 * j], wcf[2 * j + 1], -USHIFT, -USHIFT, -USHIFT, -USHIFT);
                        const uint32_t ra = gate_pair(d[0], d[1], eb[0][j], iea[j]);
                        den[j] = add_bf2(den[j], ra);
                        num[j] = fma_bf2(ra, hq[0][j], num[j]);
                    }
                    load_rows();
                }
            } while (!last);
            const int f0 = 32 * (g >> 2) + 8 * q + 2 * (g & 3);
            float sum[4];
            reduce_rows(sum, den, num);
            bool mine = true;
            if (node >= NWHOLE) {
                const uint32_t st = sb + SM_STATE + (node - NWHOLE) * 4, pa = sb + SM_PART + (node - NWHOLE) * 512 + lane * 16;
                mine = uni((int)atoms_inc_if(st, lane == 0, 0u)) != 0;
                if (!mine) {
                    sts128(pa, __float_as_uint(sum[0]), __float_as_uint(sum[1]), __float_as_uint(sum[2]), __float_as_uint(sum[3]));
                    asm volatile("fence.acq_rel.cta;" ::: "memory");
                    __syncwarp();
                    if (lane == 0) atomicAdd((int*)(smem + (st - sb)), 2);
                } else {
                    while (*(volatile int*)(smem + (st - sb)) < 4) {}
                    asm volatile("fence.acq_rel.cta;" ::: "memory");
                    const uint4 o = lds128(pa);
                    sum[0] += __uint_as_float(o.x); sum[1] += __uint_as_float(o.y);
                    sum[2] += __uint_as_float(o.z); sum[3] += __uint_as_float(o.w);
                }
            }
            if (mine) write_node(node, sum, f0);
            if (nnode < 0) break;
            node = nnode;
        }
    } else {
        float2* acc = g_acc + (size_t)cta * NPB * 64;
        __syncthreads();
        load_weights(tid, NTHREADS);
        cp_commit();
        for (int i = tid; i < NPB * 64; i += NTHREADS) acc[i] = make_float2(0.f, 0.f);
        cp_wait<0>();
        int scan_pos = bad_list ? 0 : N_EDGES;
        int pend = 0, pv = 0;
        int4 d4 = make_int4(0, 0, 0, 0);
        bool more = true;
        while (more) {
            if (bad_list) {
                __syncthreads();
                if (tid < 80) s_ncnt[tid] = 0;
                __syncthreads();
                while (true) {
                    const int dd[4] = {d4.x, d4.y, d4.z, d4.w};
                    #pragma unroll
                    for (int j = 0; j < 4; j++) {
                        if (pend >> j & 1) {
                            const int dl = dd[j] - node0;
                            const int r = atomicAdd(&s_ncnt[dl], 1);
                            if (r < CAPN) {
                                const int e = pv * 4 + j;
                                sts64(sb + SM_LIST + dl * LIST_LD + r * 8, (uint32_t)__ldg(src + e) << 8, (uint32_t)e * 32u);
                                pend &= ~(1 << j);
                            }
                        }
                    }
                    if (__syncthreads_or(pend)) break;
                    if (scan_pos >= N_EDGES) { more = false; break; }
                    pv = (scan_pos >> 2) + tid;
                    if (pv < N_EDGES / 4) {
                        d4 = __ldg((const int4*)dst + pv);
                        pend = ((uint32_t)(d4.x - node0) < NPB ? 1 : 0) | ((uint32_t)(d4.y - node0) < NPB ? 2 : 0)
                             | ((uint32_t)(d4.z - node0) < NPB ? 4 : 0) | ((uint32_t)(d4.w - node0) < NPB ? 8 : 0);
                    }
                    scan_pos += NTHREADS * 4;
                }
            } else {
                more = false;
                __syncthreads();
            }
            const uint32_t wrow = sb + SM_W + (lane & 15) * 128;
            #pragma unroll 1
            for (int job = warp; job < NPB * 4; job += NWARPS) {
                const int n = job >> 2, jp = job & 3;
                const int cnt = min(s_ncnt[n], CAPN);
                if (cnt == 0) continue;
                const uint32_t wa = wrow + (((2 * jp + (lane >> 4)) ^ (lane & 7)) << 4);
                float ca[8] = {0.f, 0.f, 0.f, 0.f, 0.f, 0.f, 0.f, 0.f};
                #pragma unroll
                for (int k = 0; k < 4; k++) {
                    const uint32_t a0 = lds32(sb + SM_XOWN + n * 128 + (((2 * k) ^ (n & 7)) << 4) + q * 4);
                    const uint32_t a2 = lds32(sb + SM_XOWN + n * 128 + (((2 * k + 1) ^ (n & 7)) << 4) + q * 4);
                    uint32_t b[4];
                    ldsm_x4_t(b, wa + WS_A + k * 2048);
                    mma_k16(&ca[0], a0, a0, a2, a2, b[0], b[1], ca[0], ca[1], ca[2], ca[3]);
                    mma_k16(&ca[4], a0, a0, a2, a2, b[2], b[3], ca[4], ca[5], ca[6], ca[7]);
                }
                float sd[4] = {0.f, 0.f, 0.f, 0.f}, sn[4] = {0.f, 0.f, 0.f, 0.f};
                #pragma unroll 1
                for (int i0 = 0; i0 < cnt; i0 += 16) {
                    const bool v0 = i0 + g < cnt, v1 = i0 + g + 8 < cnt;
                    const uint2 r0 = lds64(sb + SM_LIST + n * LIST_LD + (v0 ? i0 + g : 0) * 8);
                    const uint2 r1 = lds64(sb + SM_LIST + n * LIST_LD + (v1 ? i0 + g + 8 : 0) * 8);
                    const uint32_t* x0 = (const uint32_t*)((const char*)x + (r0.x >> 1)) + q;
                    const uint32_t* x1 = (const uint32_t*)((const char*)x + (r1.x >> 1)) + q;
                    const uint32_t* e0 = (const uint32_t*)((const char*)e_attr + r0.y) + q;
                    const uint32_t* e1 = (const uint32_t*)((const char*)e_attr + r1.y) + q;
                    float gg[8], hh[8] = {0.f, 0.f, 0.f, 0.f, 0.f, 0.f, 0.f, 0.f};
                    uint32_t b[4];
                    {
                        const uint32_t a0 = __ldg(e0), a1 = __ldg(e1), a2 = __ldg(e0 + 4), a3 = __ldg(e1 + 4);
                        ldsm_x4_t(b, wa + WS_C);
                        mma_k16(&gg[0], a0, a1, a2, a3, b[0], b[1], ca[0], ca[1], ca[2], ca[3]);
                        mma_k16(&gg[4], a0, a1, a2, a3, b[2], b[3], ca[4], ca[5], ca[6], ca[7]);
                    }
                    #pragma unroll
                    for (int k = 0; k < 4; k++) {
                        const uint32_t a0 = __ldg(x0 + 8 * k), a1 = __ldg(x1 + 8 * k), a2 = __ldg(x0 + 8 * k + 4), a3 = __ldg(x1 + 8 * k + 4);
                        ldsm_x4_t(b, wa + WS_B + k * 2048);
                        mma_k16(&gg[0], a0, a1, a2, a3, b[0], b[1], gg[0], gg[1], gg[2], gg[3]);
                        mma_k16(&gg[4], a0, a1, a2, a3, b[2], b[3], gg[4], gg[5], gg[6], gg[7]);
                        ldsm_x4_t(b, wa + WS_V + k * 2048);
                        mma_k16(&hh[0], a0, a1, a2, a3, b[0], b[1], hh[0], hh[1], hh[2], hh[3]);
                        mma_k16(&hh[4], a0, a1, a2, a3, b[2], b[3], hh[4], hh[5], hh[6], hh[7]);
                    }
                    #pragma unroll
                    for (int i = 0; i < 8; i++) {
                        const float eta = ((i & 2) ? v1 : v0) ? 1.0f / (1.0f + ex2f(gg[i] * -L2E)) : 0.f;
                        const int o = (i >> 2) * 2 + (i & 1);
                        sd[o] += eta;
                        sn[o] = fmaf(eta, hh[i], sn[o]);
                    }
                }
                #pragma unroll
                for (int i = 0; i < 4; i++) {
                    #pragma unroll
                    for (int o = 4; o < 32; o <<= 1) {
                        sd[i] += __shfl_xor_sync(0xffffffffu, sd[i], o);
                        sn[i] += __shfl_xor_sync(0xffffffffu, sn[i], o);
                    }
                }
                if (g == 0) {
                    #pragma unroll
                    for (int i = 0; i < 4; i++) {
                        float2* pa = acc + n * 64 + jp * 16 + (i >> 1) * 8 + 2 * q + (i & 1);
                        *pa = make_float2(pa->x + sd[i], pa->y + sn[i]);
                    }
                }
            }
        }
        __syncthreads();
        for (int i = tid; i < NPB * 64; i += NTHREADS) {
            const int n = i >> 6, f = i & 63;
            if (node0 + n < N_NODES) {
                const float2 a = acc[i];
                const float u = __bfloat162float(*(const __nv_bfloat16*)(smem + SM_U + n * U_LD + f * 2));
                const float xv = __bfloat162float(*(const __nv_bfloat16*)(smem + SM_XOWN + n * 128 + (((f >> 3) ^ (n & 7)) << 4) + (f & 7) * 2));
                out[(size_t)(node0 + n) * 64 + f] = __float2bfloat16(xv + fmaxf(u + a.y / (a.x + 1e-6f), 0.f));
            }
        }
    }
}

}

extern "C" void kernel_launch(void* const* d_in, const int* in_sizes, int n_in, void* d_out, int out_size) {
    (void)in_sizes; (void)n_in; (void)out_size;
    constexpr int SMEM = SM_TOTAL;
    cudaFuncSetAttribute(gatedgcn_kernel, cudaFuncAttributeMaxDynamicSharedMemorySize, SMEM);
    gatedgcn_kernel<<<NB, NTHREADS, SMEM>>>(
        (const __nv_bfloat16*)d_in[0], (const __nv_bfloat16*)d_in[1], (const int*)d_in[2], (const int*)d_in[3],
        (const __nv_bfloat16*)d_in[4], (const __nv_bfloat16*)d_in[5], (const __nv_bfloat16*)d_in[6],
        (const __nv_bfloat16*)d_in[7], (const __nv_bfloat16*)d_in[8], (__nv_bfloat16*)d_out);
}
```
